```python
import torch

def _softmax(x, axis=-1):
    return torch.softmax(x, dim=axis)
def _gelu(x):
    return torch.nn.functional.gelu(x, approximate="tanh")
def _silu(x):
    return torch.nn.functional.silu(x)
def _sigmoid(x):
    return torch.sigmoid(x)
def _layernorm(x, axis=-1, eps=1e-5):
    m = x.mean(dim=axis, keepdim=True)
    v = x.var(dim=axis, keepdim=True, unbiased=False)
    return (x - m) / torch.sqrt(v + eps)
def _scatter_add(tgt, idx, src, axis=0):
    return tgt.clone().index_add_(axis, idx, src)
def _segment_sum(src, seg, n):
    out = torch.zeros((n,) + src.shape[1:], dtype=src.dtype)
    return out.index_add_(0, seg, src)
def _pad(x, pw):
    flat = tuple(v for pair in reversed(pw) for v in pair)
    return torch.nn.functional.pad(x, flat)

kernel_name = 'sequential_preLN__softmax_full_mha__dense_activation_silu__prompt'

def setup_inputs():

    _w = (lambda a: (lambda t: t.to(torch.bfloat16) if t.is_floating_point() else t)(torch.as_tensor(a)))
    def _A_setup():
        B, S, D = 1, 2048, 448
        return {
            "x": _w((lambda *s: torch.randn(*s, dtype=torch.bfloat16) * 0.05)(B, S, D)),
            "wqkv": _w((lambda *s: torch.randn(*s, dtype=torch.bfloat16) * 0.05)(D, 3 * D)),
            "wo": _w((lambda *s: torch.randn(*s, dtype=torch.bfloat16) * 0.05)(D, D)),
        }
    _A_in = _A_setup()

    def _B_setup():
        B, S, D, F = 1, 2048, 448, 1792
        return {
            "x": _w((lambda *s: torch.randn(*s, dtype=torch.bfloat16) * 0.05)(B, S, D)),
            "w1": _w((lambda *s: torch.randn(*s, dtype=torch.bfloat16) * 0.8)(D, F) * (D ** -0.5)),
            "w2": _w((lambda *s: torch.randn(*s, dtype=torch.bfloat16) * 0.2)(F, D) * (F ** -0.5)),
        }
    _B_in = _B_setup()

    return {
        "A_x": _A_in["x"],
        "A_wqkv": _A_in["wqkv"],
        "A_wo": _A_in["wo"],
        "B_x": _B_in["x"],
        "B_w1": _B_in["w1"],
        "B_w2": _B_in["w2"],
    }

def reference(A_x, A_wqkv, A_wo, B_x, B_w1, B_w2):
    def _A_ref(x, wqkv, wo):
        B, S, D = x.shape
        H = 16; Dh = D // H
        qkv = (lambda x, *d: x.permute(*d))((x @ wqkv).reshape(B, S, 3, H, Dh), 2, 0, 3, 1, 4)
        q, k, v = qkv[0], qkv[1], qkv[2]
        scale = Dh ** -0.5
        scores = torch.einsum("bhqd,bhkd->bhqk", q, k) * scale
        p = _softmax(scores, axis=-1)
        o = torch.einsum("bhqk,bhkd->bhqd", p, v)
        return (lambda x, *d: x.permute(*d))(o, 0, 2, 1, 3).reshape(B, S, D) @ wo

    def _B_ref(x, w1, w2):
        h = torch.einsum("bsd,df->bsf", x, w1)
        h = _silu(h)
        out = torch.einsum("bsf,fd->bsd", h, w2)
        return out

    x = A_x
    h = x + _A_ref(_layernorm(x, axis=-1), A_wqkv, A_wo)
    h2 = h + _B_ref(_layernorm(h, axis=-1), B_w1, B_w2)
    return h2
```

```cpp
#include <cuda_runtime.h>
#include <cuda.h>
#include <cuda_bf16.h>
#include <cuda_fp16.h>
#include <stdint.h>

namespace {

constexpr int NS = 2048, ND = 448, NF = 1792;
constexpr int NTHREADS = 640;
#define POLY_MASK 0x5AD6B5ADu
#define POLY_DEG 2

constexpr uint32_t SM_A = 0;
constexpr uint32_t SM_G = 114688;
constexpr uint32_t SM_R = 172032;
constexpr uint32_t SM_W = 131072;
constexpr uint32_t SM_KV0 = 98304;
constexpr uint32_t SM_BAR = 221184;
constexpr uint32_t SM_TR = SM_BAR + 1024;
constexpr uint32_t SM_CS0 = SM_TR + 128;
constexpr uint32_t SM_CS1 = SM_CS0 + 384;
constexpr uint32_t SM_RED = SM_CS1 + 1024;
constexpr uint32_t SM_EP = SM_RED + 3072;
constexpr uint32_t SM_TOTAL = SM_EP + 16;

enum : int {
  B_XFULL = 0, B_XREL = 7, B_KVFULL = 11, B_KVREL = 19, B_CS0 = 27, B_AFREE1 = 28, B_OFULL = 29, B_WOFULL = 36,
  B_AFREE2 = 37, B_WODONE = 38, B_HFULL = 39, B_WFULL = 46, B_WREL = 74, B_GFULL = 102, B_GFREE_R = 109,
  B_AFREE3_L = 110, B_AFREE3_R = 111, B_CS1 = 112, B_COUNT = 113
};

__device__ uint32_t g_epoch[128];
__device__ uint32_t g_abort;
__device__ __align__(128) unsigned char g_kv[16 * 8 * 32768];
__device__ __align__(16) float g_kvtr[16 * 8 * 4];
__device__ uint32_t g_flagKV[16 * 8 * 8];
__device__ __align__(128) __nv_bfloat16 g_O[NS * ND];
__device__ uint32_t g_cntO[16 * 8];
__device__ __align__(128) unsigned char g_h[16 * 7 * 16384];
__device__ uint32_t g_flagH[16 * 8 * 8];
__device__ uint2 g_st1[NS];
__device__ uint2 g_cs0[16 * 8 * 48];
__device__ uint2 g_st2[7 * NS];
__device__ uint2 g_cs1[8 * 16 * 128];
__device__ uint4 g_part[16 * 2 * 4 * 4 * 4 * 4 * 128];
#define PMARK(role, i) do {} while (0)
#define PROF_PARAM
#define PROF_ARG

__device__ __forceinline__ void wg_fence() { asm volatile("wgmma.fence.sync.aligned;" ::: "memory"); }
__device__ __forceinline__ void wg_commit() { asm volatile("wgmma.commit_group.sync.aligned;" ::: "memory"); }
template <int N> __device__ __forceinline__ void wg_wait() { asm volatile("wgmma.wait_group.sync.aligned %0;" ::"n"(N) : "memory"); }
template <int N> __device__ __forceinline__ void pin(float (&d)[N]) {
#pragma unroll
  for (int i = 0; i < N; i++) asm volatile("" : "+f"(d[i])::"memory");
}
template <int N> __device__ __forceinline__ void pin(uint32_t (&d)[N]) {
#pragma unroll
  for (int i = 0; i < N; i++) asm volatile("" : "+r"(d[i])::"memory");
}
__device__ __forceinline__ uint64_t mkdesc(uint32_t addr, uint32_t lbo, uint32_t sbo, uint32_t sw) {
  return ((uint64_t)((sbo >> 4) | (sw << 30)) << 32) | (uint64_t)(((addr & 0x3FFFFu) >> 4) | ((lbo >> 4) << 16));
}
__device__ __forceinline__ uint64_t dadd(uint64_t d, uint32_t off) {
  return (d & 0xFFFFFFFF00000000ull) | (uint32_t)((uint32_t)d + (off >> 4));
}
__device__ __forceinline__ bool timed_out(uint32_t& n) {
  if ((++n & 0xFFFu) != 0) return false;
  if (n > (1u << 25)) asm volatile("st.relaxed.gpu.global.u32 [%0], %1;" ::"l"(&g_abort), "r"(1) : "memory");
  uint32_t v;
  asm volatile("ld.relaxed.gpu.global.u32 %0, [%1];" : "=r"(v) : "l"(&g_abort) : "memory");
  return v != 0;
}
__device__ __forceinline__ void mbar_init(uint32_t b, int c) { asm volatile("mbarrier.init.shared::cta.b64 [%0], %1;" ::"r"(b), "r"(c) : "memory"); }
__device__ __forceinline__ void mbar_expect(uint32_t b, uint32_t bytes) {
  asm volatile("mbarrier.arrive.expect_tx.shared::cta.b64 _, [%0], %1;" ::"r"(b), "r"(bytes) : "memory");
}
__device__ __forceinline__ void mbar_arrive(uint32_t b) { asm volatile("mbarrier.arrive.shared::cta.b64 _, [%0];" ::"r"(b) : "memory"); }
__device__ __forceinline__ uint32_t mapa(uint32_t a, uint32_t rank) {
  uint32_t r;
  asm("mapa.shared::cluster.u32 %0, %1, %2;" : "=r"(r) : "r"(a), "r"(rank));
  return r;
}
__device__ __forceinline__ void mbar_arrive_remote(uint32_t rb) {
  asm volatile("mbarrier.arrive.release.cluster.shared::cluster.b64 _, [%0];" ::"r"(rb) : "memory");
}
__device__ __forceinline__ bool mbar_try(uint32_t b) {
  uint32_t ok;
  asm volatile("{\n.reg .pred p;\nmbarrier.try_wait.parity.acquire.cluster.shared::cta.b64 p, [%1], 0;\nselp.u32 %0, 1, 0, p;\n}"
               : "=r"(ok) : "r"(b) : "memory");
  return ok;
}
__device__ __forceinline__ void mbar_wait(uint32_t b) {
  if (mbar_try(b)) return;
  uint32_t t0 = 0;
  while (!mbar_try(b) && !timed_out(t0)) {}
}
__device__ __forceinline__ void bar_sync(int id, int n) { asm volatile("bar.sync %0, %1;" ::"r"(id), "r"(n) : "memory"); }
__device__ __forceinline__ void fence_async_smem() { asm volatile("fence.proxy.async.shared::cta;" ::: "memory"); }
__device__ __forceinline__ void fence_async_all() { asm volatile("fence.proxy.async;" ::: "memory"); }
__device__ __forceinline__ void fence_gpu() { asm volatile("fence.acq_rel.gpu;" ::: "memory"); }
__device__ __forceinline__ void tma2d(uint32_t dst, const CUtensorMap* tm, int c0, int c1, uint32_t bar) {
  asm volatile("cp.async.bulk.tensor.2d.shared::cluster.global.mbarrier::complete_tx::bytes [%0], [%1, {%3, %4}], [%2];"
               ::"r"(dst), "l"(tm), "r"(bar), "r"(c0), "r"(c1) : "memory");
}
__device__ __forceinline__ void tma2d_mc(uint32_t dst, const CUtensorMap* tm, int c0, int c1, uint32_t bar) {
  asm volatile("cp.async.bulk.tensor.2d.shared::cluster.global.mbarrier::complete_tx::bytes.multicast::cluster [%0], [%1, {%3, %4}], [%2], %5;"
               ::"r"(dst), "l"(tm), "r"(bar), "r"(c0), "r"(c1), "h"((uint16_t)3) : "memory");
}
__device__ __forceinline__ void tma3d(uint32_t dst, const CUtensorMap* tm, int c0, int c1, int c2, uint32_t bar) {
  asm volatile("cp.async.bulk.tensor.3d.shared::cluster.global.mbarrier::complete_tx::bytes [%0], [%1, {%3, %4, %5}], [%2];"
               ::"r"(dst), "l"(tm), "r"(bar), "r"(c0), "r"(c1), "r"(c2) : "memory");
}
__device__ __forceinline__ void bulk_g2s(uint32_t dst, const void* src, uint32_t bytes, uint32_t bar) {
  asm volatile("cp.async.bulk.shared::cluster.global.mbarrier::complete_tx::bytes [%0], [%1], %2, [%3];"
               ::"r"(dst), "l"(src), "r"(bytes), "r"(bar) : "memory");
}
__device__ __forceinline__ void bulk_g2s_mc(uint32_t dst, const void* src, uint32_t bytes, uint32_t bar) {
  asm volatile("cp.async.bulk.shared::cluster.global.mbarrier::complete_tx::bytes.multicast::cluster [%0], [%1], %2, [%3], %4;"
               ::"r"(dst), "l"(src), "r"(bytes), "r"(bar), "h"((uint16_t)3) : "memory");
}
__device__ __forceinline__ void bulk_s2g(void* dst, uint32_t src, uint32_t bytes) {
  asm volatile("cp.async.bulk.global.shared::cta.bulk_group [%0], [%1], %2;" ::"l"(dst), "r"(src), "r"(bytes) : "memory");
}
__device__ __forceinline__ void bulk_s2peer(uint32_t rdst, uint32_t src, uint32_t bytes, uint32_t rbar) {
  asm volatile("cp.async.bulk.shared::cluster.shared::cta.mbarrier::complete_tx::bytes [%0], [%1], %2, [%3];"
               ::"r"(rdst), "r"(src), "r"(bytes), "r"(rbar) : "memory");
}
__device__ __forceinline__ void bulk_commit_wait() {
  asm volatile("cp.async.bulk.commit_group;\ncp.async.bulk.wait_group 0;" ::: "memory");
}
__device__ __forceinline__ void l2_prefetch(const void* p, uint32_t bytes) {
  asm volatile("cp.async.bulk.prefetch.L2.global [%0], %1;" ::"l"(p), "r"(bytes) : "memory");
}
__device__ __forceinline__ uint32_t ld_acquire(const uint32_t* p) {
  uint32_t v;
  asm volatile("ld.acquire.gpu.global.u32 %0, [%1];" : "=r"(v) : "l"(p) : "memory");
  return v;
}
__device__ __forceinline__ void red_add(uint32_t* p) { asm volatile("red.relaxed.gpu.global.add.u32 [%0], 1;" ::"l"(p) : "memory"); }
__device__ __forceinline__ void wait_count(const uint32_t* p, uint32_t target) {
  uint32_t t0 = 0;
  while ((int)(ld_acquire(p) - target) < 0 && !timed_out(t0)) {}
}
__device__ __forceinline__ uint32_t tagw(float v, uint32_t par) { return (__float_as_uint(v) & ~1u) | par; }
__device__ __forceinline__ void st_tag2(uint2* p, float a, float b, uint32_t par) {
  asm volatile("st.relaxed.gpu.global.v2.u32 [%0], {%1, %2};" ::"l"(p), "r"(tagw(a, par)), "r"(tagw(b, par)) : "memory");
}
__device__ __forceinline__ uint2 ld_rlx2(const uint2* p) {
  uint2 v;
  asm volatile("ld.relaxed.gpu.global.v2.u32 {%0, %1}, [%2];" : "=r"(v.x), "=r"(v.y) : "l"(p) : "memory");
  return v;
}
__device__ __forceinline__ uint4 ld_rlx4(const uint4* p) {
  uint4 v;
  asm volatile("ld.relaxed.gpu.global.v4.u32 {%0, %1, %2, %3}, [%4];" : "=r"(v.x), "=r"(v.y), "=r"(v.z), "=r"(v.w) : "l"(p) : "memory");
  return v;
}
__device__ __forceinline__ float2 poll_tag2(const uint2* p, uint2 v, uint32_t par) {
  uint32_t t0 = 0;
  while ((((v.x ^ par) | (v.y ^ par)) & 1u) != 0 && !timed_out(t0)) v = ld_rlx2(p);
  return make_float2(__uint_as_float(v.x), __uint_as_float(v.y));
}
__device__ __forceinline__ uint32_t pack_h2(float lo, float hi) {
  uint32_t r;
  asm("cvt.rn.f16x2.f32 %0, %1, %2;" : "=r"(r) : "f"(hi), "f"(lo));
  return r;
}
__device__ __forceinline__ uint32_t pack_b2(float lo, float hi) {
  uint32_t r;
  asm("cvt.rn.bf16x2.f32 %0, %1, %2;" : "=r"(r) : "f"(hi), "f"(lo));
  return r;
}
__device__ __forceinline__ float b_lo(uint32_t v) { return __uint_as_float(v << 16); }
__device__ __forceinline__ float b_hi(uint32_t v) { return __uint_as_float(v & 0xFFFF0000u); }
__device__ __forceinline__ void stsm4(uint32_t addr, uint32_t a, uint32_t b, uint32_t c, uint32_t d) {
  asm volatile("stmatrix.sync.aligned.m8n8.x4.shared.b16 [%0], {%1, %2, %3, %4};" ::"r"(addr), "r"(a), "r"(b), "r"(c), "r"(d) : "memory");
}
__device__ __forceinline__ float2 lds_f2(uint32_t a) {
  float2 v;
  asm volatile("ld.shared.v2.f32 {%0, %1}, [%2];" : "=f"(v.x), "=f"(v.y) : "r"(a) : "memory");
  return v;
}
__device__ __forceinline__ uint32_t lds_u32(uint32_t a) {
  uint32_t v;
  asm volatile("ld.shared.u32 %0, [%1];" : "=r"(v) : "r"(a) : "memory");
  return v;
}
__device__ __forceinline__ void sts_f2(uint32_t a, float x, float y) { asm volatile("st.shared.v2.f32 [%0], {%1, %2};" ::"r"(a), "f"(x), "f"(y) : "memory"); }
__device__ __forceinline__ float quad_sum(float v) {
  v += __shfl_xor_sync(0xffffffffu, v, 1);
  return v + __shfl_xor_sync(0xffffffffu, v, 2);
}

__device__ __forceinline__ int fresh_tid() {
  int t;
  asm volatile("mov.u32 %0, %%tid.x;" : "=r"(t));
  return t;
}
__device__ __forceinline__ void sts_u32(uint32_t a, uint32_t v) { asm volatile("st.shared.u32 [%0], %1;" ::"r"(a), "r"(v) : "memory"); }

__device__ __forceinline__ void mma_ss_n96_bf16_f32(float (&d)[48], uint64_t da, uint64_t db, int acc) {
  asm volatile(
      "{\n.reg .pred p;\nsetp.ne.b32 p, %50, 0;\n"
      "wgmma.mma_async.sync.aligned.m64n96k16.f32.bf16.bf16 {"
      "%0, %1, %2, %3, %4, %5, %6, %7, %8, %9, %10, %11, %12, %13, %14, %15, %16, %17, %18, %19, %20, %21, %22, "
      "%23, %24, %25, %26, %27, %28, %29, %30, %31, %32, %33, %34, %35, %36, %37, %38, %39, %40, %41, %42, %43, "
      "%44, %45, %46, %47"
      "}, %48, %49, p, 1, 1, 0, 1;\n}\n"
      : "+f"(d[0]), "+f"(d[1]), "+f"(d[2]), "+f"(d[3]), "+f"(d[4]), "+f"(d[5]), "+f"(d[6]), "+f"(d[7]),
        "+f"(d[8]), "+f"(d[9]), "+f"(d[10]), "+f"(d[11]), "+f"(d[12]), "+f"(d[13]), "+f"(d[14]), "+f"(d[15]),
        "+f"(d[16]), "+f"(d[17]), "+f"(d[18]), "+f"(d[19]), "+f"(d[20]), "+f"(d[21]), "+f"(d[22]), "+f"(d[23]),
        "+f"(d[24]), "+f"(d[25]), "+f"(d[26]), "+f"(d[27]), "+f"(d[28]), "+f"(d[29]), "+f"(d[30]), "+f"(d[31]),
        "+f"(d[32]), "+f"(d[33]), "+f"(d[34]), "+f"(d[35]), "+f"(d[36]), "+f"(d[37]), "+f"(d[38]), "+f"(d[39]),
        "+f"(d[40]), "+f"(d[41]), "+f"(d[42]), "+f"(d[43]), "+f"(d[44]), "+f"(d[45]), "+f"(d[46]), "+f"(d[47])
      : "l"(da), "l"(db), "r"(acc));
}
__device__ __forceinline__ void mma_ss_n64_bf16_f32(float (&d)[32], uint64_t da, uint64_t db, int acc) {
  asm volatile(
      "{\n.reg .pred p;\nsetp.ne.b32 p, %34, 0;\n"
      "wgmma.mma_async.sync.aligned.m64n64k16.f32.bf16.bf16 {"
      "%0, %1, %2, %3, %4, %5, %6, %7, %8, %9, %10, %11, %12, %13, %14, %15, %16, %17, %18, %19, %20, %21, %22, "
      "%23, %24, %25, %26, %27, %28, %29, %30, %31"
      "}, %32, %33, p, 1, 1, 0, 1;\n}\n"
      : "+f"(d[0]), "+f"(d[1]), "+f"(d[2]), "+f"(d[3]), "+f"(d[4]), "+f"(d[5]), "+f"(d[6]), "+f"(d[7]),
        "+f"(d[8]), "+f"(d[9]), "+f"(d[10]), "+f"(d[11]), "+f"(d[12]), "+f"(d[13]), "+f"(d[14]), "+f"(d[15]),
        "+f"(d[16]), "+f"(d[17]), "+f"(d[18]), "+f"(d[19]), "+f"(d[20]), "+f"(d[21]), "+f"(d[22]), "+f"(d[23]),
        "+f"(d[24]), "+f"(d[25]), "+f"(d[26]), "+f"(d[27]), "+f"(d[28]), "+f"(d[29]), "+f"(d[30]), "+f"(d[31])
      : "l"(da), "l"(db), "r"(acc));
}
__device__ __forceinline__ void mma_ss_n128_bf16_f32(float (&d)[64], uint64_t da, uint64_t db, int acc) {
  asm volatile(
      "{\n.reg .pred p;\nsetp.ne.b32 p, %66, 0;\n"
      "wgmma.mma_async.sync.aligned.m64n128k16.f32.bf16.bf16 {"
      "%0, %1, %2, %3, %4, %5, %6, %7, %8, %9, %10, %11, %12, %13, %14, %15, %16, %17, %18, %19, %20, %21, %22, "
      "%23, %24, %25, %26, %27, %28, %29, %30, %31, %32, %33, %34, %35, %36, %37, %38, %39, %40, %41, %42, %43, "
      "%44, %45, %46, %47, %48, %49, %50, %51, %52, %53, %54, %55, %56, %57, %58, %59, %60, %61, %62, %63"
      "}, %64, %65, p, 1, 1, 0, 1;\n}\n"
      : "+f"(d[0]), "+f"(d[1]), "+f"(d[2]), "+f"(d[3]), "+f"(d[4]), "+f"(d[5]), "+f"(d[6]), "+f"(d[7]),
        "+f"(d[8]), "+f"(d[9]), "+f"(d[10]), "+f"(d[11]), "+f"(d[12]), "+f"(d[13]), "+f"(d[14]), "+f"(d[15]),
        "+f"(d[16]), "+f"(d[17]), "+f"(d[18]), "+f"(d[19]), "+f"(d[20]), "+f"(d[21]), "+f"(d[22]), "+f"(d[23]),
        "+f"(d[24]), "+f"(d[25]), "+f"(d[26]), "+f"(d[27]), "+f"(d[28]), "+f"(d[29]), "+f"(d[30]), "+f"(d[31]),
        "+f"(d[32]), "+f"(d[33]), "+f"(d[34]), "+f"(d[35]), "+f"(d[36]), "+f"(d[37]), "+f"(d[38]), "+f"(d[39]),
        "+f"(d[40]), "+f"(d[41]), "+f"(d[42]), "+f"(d[43]), "+f"(d[44]), "+f"(d[45]), "+f"(d[46]), "+f"(d[47]),
        "+f"(d[48]), "+f"(d[49]), "+f"(d[50]), "+f"(d[51]), "+f"(d[52]), "+f"(d[53]), "+f"(d[54]), "+f"(d[55]),
        "+f"(d[56]), "+f"(d[57]), "+f"(d[58]), "+f"(d[59]), "+f"(d[60]), "+f"(d[61]), "+f"(d[62]), "+f"(d[63])
      : "l"(da), "l"(db), "r"(acc));
}
template <int ACC>
__device__ __forceinline__ void mma_rs_n128_f16_f16(uint32_t (&d)[32], uint32_t a0, uint32_t a1, uint32_t a2, uint32_t a3, uint64_t db) {
  asm volatile(
      "{\n.reg .pred p;\nsetp.ne.b32 p, %37, 0;\n"
      "wgmma.mma_async.sync.aligned.m64n128k16.f16.f16.f16 {"
      "%0, %1, %2, %3, %4, %5, %6, %7, %8, %9, %10, %11, %12, %13, %14, %15, %16, %17, %18, %19, %20, %21, %22, "
      "%23, %24, %25, %26, %27, %28, %29, %30, %31"
      "}, {%32, %33, %34, %35}, %36, p, 1, 1, 0;\n}\n"
      : "+r"(d[0]), "+r"(d[1]), "+r"(d[2]), "+r"(d[3]), "+r"(d[4]), "+r"(d[5]), "+r"(d[6]), "+r"(d[7]),
        "+r"(d[8]), "+r"(d[9]), "+r"(d[10]), "+r"(d[11]), "+r"(d[12]), "+r"(d[13]), "+r"(d[14]), "+r"(d[15]),
        "+r"(d[16]), "+r"(d[17]), "+r"(d[18]), "+r"(d[19]), "+r"(d[20]), "+r"(d[21]), "+r"(d[22]), "+r"(d[23]),
        "+r"(d[24]), "+r"(d[25]), "+r"(d[26]), "+r"(d[27]), "+r"(d[28]), "+r"(d[29]), "+r"(d[30]), "+r"(d[31])
      : "r"(a0), "r"(a1), "r"(a2), "r"(a3), "l"(db), "n"(ACC));
}
template <int ACC>
__device__ __forceinline__ void mma_rs_n32_f16_f16(uint32_t (&d)[8], uint32_t a0, uint32_t a1, uint32_t a2, uint32_t a3, uint64_t db) {
  asm volatile(
      "{\n.reg .pred p;\nsetp.ne.b32 p, %13, 0;\n"
      "wgmma.mma_async.sync.aligned.m64n32k16.f16.f16.f16 {"
      "%0, %1, %2, %3, %4, %5, %6, %7"
      "}, {%8, %9, %10, %11}, %12, p, 1, 1, 1;\n}\n"
      : "+r"(d[0]), "+r"(d[1]), "+r"(d[2]), "+r"(d[3]), "+r"(d[4]), "+r"(d[5]), "+r"(d[6]), "+r"(d[7])
      : "r"(a0), "r"(a1), "r"(a2), "r"(a3), "l"(db), "n"(ACC));
}

__device__ __forceinline__ uint32_t exp2_mufu(uint32_t x) {
  uint32_t r;
  asm("ex2.approx.f16x2 %0, %1;" : "=r"(r) : "r"(x));
  return r;
}
__device__ __forceinline__ uint32_t exp2_poly(uint32_t x) {
  uint32_t t, nn, f, q, e;
  asm("add.rn.f16x2 %0, %1, %2;" : "=r"(t) : "r"(x), "r"(0x66206620u));
  asm("sub.rn.f16x2 %0, %1, %2;" : "=r"(nn) : "r"(0x66206620u), "r"(t));
  asm("add.rn.f16x2 %0, %1, %2;" : "=r"(f) : "r"(x), "r"(nn));
  asm("fma.rn.f16x2 %0, %1, %2, %3;" : "=r"(q) : "r"(f), "r"(0xB3A4B3A4u), "r"(0xB9A0B9A0u));
  asm("fma.rn.f16x2 %0, %1, %2, %3;" : "=r"(q) : "r"(q), "r"(f), "r"(0xBC00BC00u));
  asm("mad.lo.u32 %0, %1, 1024, %2;" : "=r"(e) : "r"(t), "r"(0u - (0x198u << 16)));
  return __viaddmin_u16x2(q, e, 0x7C007C00u);
}

template <int FIRST>
__device__ __forceinline__ void attn_tile(uint32_t (&s)[32], uint32_t (&oh)[8], const uint32_t (&q)[8], uint64_t kd, uint64_t vd) {
  uint32_t p[32];
#pragma unroll
  for (int c = 0; c < 4; c++) {
#pragma unroll
    for (int g = 8 * c; g < 8 * c + 8; g++) p[g] = ((POLY_MASK >> g) & 1) ? exp2_poly(s[g]) : exp2_mufu(s[g]);
#pragma unroll
    for (int g = 8 * c; g < 8 * c + 8; g++) asm volatile("" : "+r"(p[g])::"memory");
    wg_fence();
    if (FIRST && c == 0) mma_rs_n32_f16_f16<0>(oh, p[0], p[1], p[2], p[3], vd);
    else mma_rs_n32_f16_f16<1>(oh, p[8 * c], p[8 * c + 1], p[8 * c + 2], p[8 * c + 3], dadd(vd, 2048 * c));
    mma_rs_n32_f16_f16<1>(oh, p[8 * c + 4], p[8 * c + 5], p[8 * c + 6], p[8 * c + 7], dadd(vd, 2048 * c + 1024));
  }
  mma_rs_n128_f16_f16<0>(s, q[0], q[1], q[2], q[3], kd);
  mma_rs_n128_f16_f16<1>(s, q[4], q[5], q[6], q[7], dadd(kd, 32));
  wg_commit();
  wg_wait<0>();
  pin(p); pin(s); pin(oh);
}

__device__ __noinline__ void attention_exact(const __nv_bfloat16* __restrict__ x, const __nv_bfloat16* __restrict__ wqkv, int h, int row0) {
  const int lane = threadIdx.x & 31;
  float qv[28], m = -INFINITY, l = 0.f, o[28];
  auto project = [&](int row, int col0, float (&dst)[28]) {
    const __nv_bfloat16* xr = x + (size_t)row * ND;
    float s = 0.f;
    for (int k = 0; k < ND; k++) s += __bfloat162float(xr[k]);
    const float mu = s * (1.f / ND);
    float v = 0.f;
    for (int k = 0; k < ND; k++) { float d = __bfloat162float(xr[k]) - mu; v += d * d; }
    const float rs = 1.f / sqrtf(v * (1.f / ND) + 1e-5f);
#pragma unroll
    for (int d = 0; d < 28; d++) dst[d] = 0.f;
    for (int k = 0; k < ND; k++) {
      const float a = (__bfloat162float(xr[k]) - mu) * rs;
      const __nv_bfloat16* w = wqkv + (size_t)k * (3 * ND) + col0;
#pragma unroll
      for (int d = 0; d < 28; d++) dst[d] = fmaf(a, __bfloat162float(w[d]), dst[d]);
    }
  };
  project(row0 + (lane & 15), 28 * h, qv);
#pragma unroll
  for (int d = 0; d < 28; d++) { qv[d] *= 0.18898223650461362f; o[d] = 0.f; }
  for (int k0 = 0; k0 < NS; k0 += 32) {
    float kv[28], vv[28];
    project(k0 + lane, ND + 28 * h, kv);
    project(k0 + lane, 2 * ND + 28 * h, vv);
    for (int t = 0; t < 32; t++) {
      float s = 0.f;
#pragma unroll
      for (int d = 0; d < 28; d++) s = fmaf(qv[d], __shfl_sync(0xffffffffu, kv[d], t), s);
      const float mn = fmaxf(m, s);
      const float corr = expf(m - mn), p = expf(s - mn);
      m = mn;
      l = l * corr + p;
#pragma unroll
      for (int d = 0; d < 28; d++) o[d] = o[d] * corr + p * __shfl_sync(0xffffffffu, vv[d], t);
    }
  }
  if (lane < 16) {
#pragma unroll
    for (int d = 0; d < 28; d++) g_O[(size_t)(row0 + lane) * ND + 28 * h + d] = __float2bfloat16(o[d] / l);
  }
}

template <int N> __device__ __forceinline__ void mma_ss(float (&d)[N / 2], uint64_t da, uint64_t db, int acc) {
  if constexpr (N == 64) mma_ss_n64_bf16_f32(d, da, db, acc);
  else mma_ss_n128_bf16_f32(d, da, db, acc);
}
__device__ __forceinline__ uint32_t wslot(int s) {
  if (s >= 3 && s <= 5) return SM_G + (s - 3) * 16384;
  if (s >= 17 && s <= 19) return SM_A + (s - 13) * 16384;
  if (s >= 23 && s <= 25) return SM_A + (s - 19) * 16384;
  if (s >= 26) s -= 6;
  if (s >= 20) s -= 6;
  return SM_R + (s % 3) * 16384;
}
__device__ __forceinline__ uint32_t gslot(int kap) {
  return kap == 0 ? SM_G : kap == 1 ? SM_G + 16384 : kap == 4 ? SM_G + 32768 : SM_A + (kap - 2 - (kap > 4)) * 16384;
}
__device__ __forceinline__ int hchunk(int j, int t) { int c = (j == 7 ? 6 : j) + t; return c >= 7 ? c - 7 : c; }
__device__ __forceinline__ int gchunk(int rank, int t) { return ((rank ? 0x3265104u : 0x6532410u) >> (4 * t)) & 7; }
__device__ __forceinline__ int f2stage(int pair, int t) { return t < 3 ? 14 + 3 * pair + t : t < 5 ? 17 + 2 * pair + t : 19 + 2 * pair + t; }

template <int N1, int N2>
__device__ __forceinline__ void ffn(uint32_t sb, int g, int j, __nv_bfloat16* __restrict__ out PROF_PARAM) {
  const int tid = fresh_tid(), lane = tid & 31, wg = tid >> 7, warp4 = (tid >> 5) & 3;
  const int rank = j & 1, ii = j >> 1, pair = wg >> 1, half = wg & 1, c4 = lane & 3;
  const uint32_t bar = sb + SM_BAR, par = lds_u32(sb + SM_EP) & 1;
  const int rl = 64 * half + 16 * warp4 + (lane >> 2);
  const int ocol0 = 64 * (rank ? 3 + 2 * pair : 2 * pair);
  uint32_t res[N2 / 16];
  {
    float acc[N1 / 2];
#pragma unroll 1
    for (int t = 0; t < 7; t++) {
      const int c = hchunk(j, t), s = 7 * pair + t;
      mbar_wait(bar + 8 * (B_HFULL + c));
      mbar_wait(bar + 8 * (B_WFULL + s));
      const uint64_t da = mkdesc(sb + SM_A + c * 16384 + half * 8192, 16, 1024, 1);
      const uint64_t db = mkdesc(sb + wslot(s), 8192, 1024, 1);
      wg_fence();
#pragma unroll
      for (int k = 0; k < 4; k++) mma_ss<N1>(acc, dadd(da, 32 * k), dadd(db, 2048 * k), (t | k) != 0);
      wg_commit();
      if (t > 0) {
        wg_wait<1>();
        if (lane == 0) mbar_arrive(bar + 8 * (B_WREL + s - 1));
      }
    }
    const int grow = 128 * g + rl;
    const uint2* sp = g_st2 + c4 * NS + grow;
    const int c2 = c4 < 3 ? 4 * NS : 0;
    uint2 u0 = ld_rlx2(sp), u1 = ld_rlx2(sp + 8), u2 = ld_rlx2(sp + c2), u3 = ld_rlx2(sp + c2 + 8);
    {
      const int orow = rl + 8 * (ii >> 1);
#pragma unroll
      for (int n = 0; n < N2 / 16; n++) {
        const int col = ocol0 + 8 * ((ii & 1) * (N2 / 16) + n);
        res[n] = lds_u32(sb + SM_A + (col >> 6) * 16384 + orow * 128 + ((((col >> 3) & 7) ^ (orow & 7)) << 4) + 4 * c4);
      }
    }
    wg_wait<0>();
    pin(acc);
    PMARK(wg, 12);
    __syncwarp();
    if (lane == 0) {
      mbar_arrive(bar + 8 * (B_WREL + 7 * pair + 6));
      mbar_arrive(bar + 8 * B_AFREE3_L);
      mbar_arrive_remote(mapa(bar + 8 * B_AFREE3_R, rank ^ 1));
      if (pair == 0) mbar_arrive_remote(mapa(bar + 8 * B_GFREE_R, rank ^ 1));
    }
    const float2 a0 = poll_tag2(sp, u0, par), a1 = poll_tag2(sp + 8, u1, par);
    const float2 b0 = poll_tag2(sp + c2, u2, par), b1 = poll_tag2(sp + c2 + 8, u3, par);
    const float w2 = c4 < 3 ? 1.f : 0.f;
    const float mu0 = quad_sum(a0.x + w2 * b0.x) * (1.f / 7), mu1 = quad_sum(a1.x + w2 * b1.x) * (1.f / 7);
    const float e0 = a0.x - mu0, e1 = a1.x - mu1, f0 = b0.x - mu0, f1 = b1.x - mu1;
    const float v0 = quad_sum(a0.y + 64.f * e0 * e0 + w2 * (b0.y + 64.f * f0 * f0));
    const float v1 = quad_sum(a1.y + 64.f * e1 * e1 + w2 * (b1.y + 64.f * f1 * f1));
    const float hr0 = 0.5f / sqrtf(v0 * (1.f / ND) + 1e-5f), hr1 = 0.5f / sqrtf(v1 * (1.f / ND) + 1e-5f);
    mbar_wait(bar + 8 * B_CS1);
    uint32_t gp[N1 / 4];
    const uint32_t csb = sb + SM_CS1 + (pair ? (rank ? 64 : 128) : 0) * 4 + 8 * c4;
#pragma unroll
    for (int n = 0; n < N1 / 8; n++) {
      const float2 cs = lds_f2(csb + 32 * n);
      float z[4] = {fmaf(-mu0, cs.x, acc[4 * n]) * hr0, fmaf(-mu0, cs.y, acc[4 * n + 1]) * hr0,
                    fmaf(-mu1, cs.x, acc[4 * n + 2]) * hr1, fmaf(-mu1, cs.y, acc[4 * n + 3]) * hr1};
#pragma unroll
      for (int e = 0; e < 4; e++) {
        float th;
        asm("tanh.approx.f32 %0, %1;" : "=f"(th) : "f"(z[e]));
        z[e] = fmaf(z[e], th, z[e]);
      }
      gp[2 * n] = pack_b2(z[0], z[1]);
      gp[2 * n + 1] = pack_b2(z[2], z[3]);
    }
    if (pair == 0) bar_sync(6, 256);
    else mbar_wait(bar + 8 * B_AFREE3_L);
    const int kap0 = rank ? 4 + pair : 2 * pair;
    const int srow = 64 * half + 16 * warp4 + (lane & 7) + 8 * ((lane >> 3) & 1);
#pragma unroll
    for (int n = 0; n < N1 / 16; n++) {
      const uint32_t dst = sb + gslot(kap0 + (n >> 2)) + srow * 128 + (((2 * (n & 3) + (lane >> 4)) ^ (srow & 7)) << 4);
      stsm4(dst, gp[4 * n], gp[4 * n + 1], gp[4 * n + 2], gp[4 * n + 3]);
    }
    fence_async_smem();
    bar_sync(2 + wg, 128);
    if (warp4 == 0 && lane == 0) {
#pragma unroll
      for (int n = 0; n < N1 / 64; n++) mbar_arrive(bar + 8 * (B_GFULL + kap0 + n));
      mbar_wait(bar + 8 * (pair ? B_AFREE3_R : B_GFREE_R));
#pragma unroll
      for (int n = 0; n < N1 / 64; n++) {
        const uint32_t src = sb + gslot(kap0 + n) + half * 8192;
        bulk_s2peer(mapa(src, rank ^ 1), src, 8192, mapa(bar + 8 * (B_GFULL + kap0 + n), rank ^ 1));
      }
    }
    __syncwarp();
    PMARK(wg, 13);
  }
  float acc[N2 / 2];
#pragma unroll 1
  for (int t = 0; t < 7; t++) {
    const int kap = gchunk(rank, t), s = f2stage(pair, t);
    mbar_wait(bar + 8 * (B_GFULL + kap));
    mbar_wait(bar + 8 * (B_WFULL + s));
    const uint64_t da = mkdesc(sb + gslot(kap) + half * 8192, 16, 1024, 1);
    const uint64_t db = mkdesc(sb + wslot(s), 8192, 1024, 1);
    wg_fence();
#pragma unroll
    for (int k = 0; k < 4; k++) mma_ss<N2>(acc, dadd(da, 32 * k), dadd(db, 2048 * k), (t | k) != 0);
    wg_commit();
    if (t > 0) {
      wg_wait<1>();
      if (lane == 0) mbar_arrive(bar + 8 * (B_WREL + f2stage(pair, t - 1)));
    }
  }
  wg_wait<0>();
  pin(acc);
  PMARK(wg, 14);
  asm volatile("barrier.cluster.arrive.release.aligned;" ::: "memory");
  constexpr int NQ = N2 / 32;
  float own[4 * NQ];
  uint4* pbase = g_part + (size_t)((g * 2 + rank) * 16) * 2048 + wg * 512 + (warp4 * 32 + lane);
#pragma unroll
  for (int o = 0; o < 4; o++) {
#pragma unroll
    for (int qd = 0; qd < NQ; qd++) {
      const int n = (o & 1) * (N2 / 16) + 2 * qd, e = 2 * (o >> 1);
      const float v0 = acc[4 * n + e], v1 = acc[4 * n + e + 1], v2 = acc[4 * n + 4 + e], v3 = acc[4 * n + 4 + e + 1];
      if (o == ii) {
        own[4 * qd] = v0; own[4 * qd + 1] = v1; own[4 * qd + 2] = v2; own[4 * qd + 3] = v3;
      } else {
        asm volatile("st.relaxed.gpu.global.v4.u32 [%0], {%1, %2, %3, %4};" ::"l"(pbase + (o * 4 + ii) * 2048 + qd * 128),
                     "r"(tagw(v0, par)), "r"(tagw(v1, par)), "r"(tagw(v2, par)), "r"(tagw(v3, par)) : "memory");
      }
    }
  }
  uint4 in[3 * NQ];
#pragma unroll
  for (int u = 0; u < 3; u++) {
    const uint4* src = pbase + (ii * 4 + ((ii + 1 + u) & 3)) * 2048;
#pragma unroll
    for (int qd = 0; qd < NQ; qd++) in[u * NQ + qd] = ld_rlx4(src + qd * 128);
  }
#pragma unroll
  for (int u = 0; u < 3; u++) {
    const uint4* src = pbase + (ii * 4 + ((ii + 1 + u) & 3)) * 2048;
#pragma unroll
    for (int qd = 0; qd < NQ; qd++) {
      uint4 v = in[u * NQ + qd];
      uint32_t t0 = 0;
      while ((((v.x ^ par) | (v.y ^ par) | (v.z ^ par) | (v.w ^ par)) & 1u) != 0 && !timed_out(t0)) v = ld_rlx4(src + qd * 128);
      in[u * NQ + qd] = v;
    }
  }
  __nv_bfloat16* orow = out + (size_t)(128 * g + rl + 8 * (ii >> 1)) * ND + ocol0 + (ii & 1) * (N2 / 2) + 2 * c4;
#pragma unroll
  for (int qd = 0; qd < NQ; qd++) {
    float s[4] = {own[4 * qd], own[4 * qd + 1], own[4 * qd + 2], own[4 * qd + 3]};
#pragma unroll
    for (int u = 0; u < 3; u++) {
      const uint4 v = in[u * NQ + qd];
      s[0] += __uint_as_float(v.x); s[1] += __uint_as_float(v.y); s[2] += __uint_as_float(v.z); s[3] += __uint_as_float(v.w);
    }
    *reinterpret_cast<uint32_t*>(orow + 16 * qd) = pack_b2(s[0] + b_lo(res[2 * qd]), s[1] + b_hi(res[2 * qd]));
    *reinterpret_cast<uint32_t*>(orow + 16 * qd + 8) = pack_b2(s[2] + b_lo(res[2 * qd + 1]), s[3] + b_hi(res[2 * qd + 1]));
  }
  PMARK(wg, 15);
}

__device__ __forceinline__ void phase_c(uint32_t sb, int g, int j, const __nv_bfloat16* __restrict__ x, const __nv_bfloat16* __restrict__ w1,
                                        __nv_bfloat16* __restrict__ out PROF_PARAM) {
  const int tid = fresh_tid(), lane = tid & 31, wg = tid >> 7, warp4 = (tid >> 5) & 3, c4 = lane & 3, rank = j & 1;
  const uint32_t bar = sb + SM_BAR, par = lds_u32(sb + SM_EP) & 1;
  if (wg < 2) {
    const int rl = 64 * wg + 16 * warp4 + (lane >> 2);
    if (j < 7) {
      uint32_t xr[16];
      const __nv_bfloat16* xp = x + (size_t)(128 * g + rl) * ND + 64 * j + 2 * c4;
#pragma unroll
      for (int n = 0; n < 8; n++) {
        xr[2 * n] = __ldg(reinterpret_cast<const uint32_t*>(xp + 8 * n));
        xr[2 * n + 1] = __ldg(reinterpret_cast<const uint32_t*>(xp + 8 * ND + 8 * n));
      }
      float acc[32];
      mbar_wait(bar + 8 * B_WOFULL);
#pragma unroll
      for (int c = 0; c < 7; c++) {
        mbar_wait(bar + 8 * (B_OFULL + c));
        if (c == 0) PMARK(wg, 7);
        const uint64_t da = mkdesc(sb + SM_A + c * 16384 + wg * 8192, 16, 1024, 1);
        const uint64_t db = mkdesc(sb + SM_G + c * 8192, 8192, 1024, 1);
        wg_fence();
#pragma unroll
        for (int k = 0; k < 4; k++) mma_ss_n64_bf16_f32(acc, dadd(da, 32 * k), dadd(db, 2048 * k), (c | k) != 0);
        wg_commit();
      }
      wg_wait<0>();
      pin(acc);
      PMARK(wg, 8);
      if (lane == 0) {
        mbar_arrive(bar + 8 * B_WODONE);
        mbar_arrive(bar + 8 * B_AFREE2);
        mbar_arrive_remote(mapa(bar + 8 * B_AFREE2, rank ^ 1));
      }
      uint32_t hp[16];
      float s0 = 0.f, s1 = 0.f;
#pragma unroll
      for (int n = 0; n < 8; n++) {
        hp[2 * n] = pack_b2(acc[4 * n] + b_lo(xr[2 * n]), acc[4 * n + 1] + b_hi(xr[2 * n]));
        hp[2 * n + 1] = pack_b2(acc[4 * n + 2] + b_lo(xr[2 * n + 1]), acc[4 * n + 3] + b_hi(xr[2 * n + 1]));
      }
      const int srow = 64 * wg + 16 * warp4 + (lane & 7) + 8 * ((lane >> 3) & 1);
#pragma unroll
      for (int n = 0; n < 4; n++)
        stsm4(sb + SM_A + j * 16384 + srow * 128 + (((2 * n + (lane >> 4)) ^ (srow & 7)) << 4), hp[4 * n], hp[4 * n + 1], hp[4 * n + 2], hp[4 * n + 3]);
      fence_async_smem();
      bar_sync(2 + wg, 128);
      if (warp4 == 0 && lane == 0) {
        bulk_s2g(g_h + (size_t)(g * 7 + j) * 16384 + wg * 8192, sb + SM_A + j * 16384 + wg * 8192, 8192);
        mbar_arrive(bar + 8 * (B_HFULL + j));
        bulk_commit_wait();
        fence_async_all();
        fence_gpu();
        red_add(g_flagH + (g * 8 + j) * 8);
      }
      __syncwarp();
#pragma unroll
      for (int n = 0; n < 8; n++) {
        s0 += b_lo(hp[2 * n]) + b_hi(hp[2 * n]);
        s1 += b_lo(hp[2 * n + 1]) + b_hi(hp[2 * n + 1]);
      }
      const float m0 = quad_sum(s0) * (1.f / 64), m1 = quad_sum(s1) * (1.f / 64);
      float v0 = 0.f, v1 = 0.f;
#pragma unroll
      for (int n = 0; n < 8; n++) {
        const float a = b_lo(hp[2 * n]) - m0, bq = b_hi(hp[2 * n]) - m0, cq = b_lo(hp[2 * n + 1]) - m1, d = b_hi(hp[2 * n + 1]) - m1;
        v0 += a * a + bq * bq;
        v1 += cq * cq + d * d;
      }
      v0 = quad_sum(v0);
      v1 = quad_sum(v1);
      if (c4 == 0) st_tag2(g_st2 + j * NS + 128 * g + rl, m0, v0, par);
      if (c4 == 1) st_tag2(g_st2 + j * NS + 128 * g + rl + 8, m1, v1, par);
      PMARK(wg, 9);
    } else {
      for (int c = 0; c < 7; c++) mbar_wait(bar + 8 * (B_OFULL + c));
      if (lane == 0) {
        mbar_arrive(bar + 8 * B_WODONE);
        mbar_arrive(bar + 8 * B_AFREE2);
        mbar_arrive_remote(mapa(bar + 8 * B_AFREE2, rank ^ 1));
      }
    }
  } else if (wg == 2) {
    const int t = tid & 127, w1c0 = 448 * (j >> 1) + 256 * rank;
    if (t < (rank ? 96 : 128)) {
      const __nv_bfloat16* wp = w1 + (size_t)(28 * g) * NF + w1c0 + 2 * t;
      uint32_t wv[28];
#pragma unroll
      for (int k = 0; k < 28; k++) wv[k] = __ldg(reinterpret_cast<const uint32_t*>(wp + k * NF));
      float s0 = 0.f, s1 = 0.f;
#pragma unroll
      for (int k = 0; k < 28; k++) { s0 += b_lo(wv[k]); s1 += b_hi(wv[k]); }
      st_tag2(g_cs1 + (j * 16 + g) * 128 + t, s0, s1, par);
      const uint2* p = g_cs1 + j * 16 * 128 + t;
      uint2 u[16];
#pragma unroll
      for (int k = 0; k < 16; k++) u[k] = ld_rlx2(p + 128 * k);
      s0 = s1 = 0.f;
#pragma unroll
      for (int k = 0; k < 16; k++) { const float2 v = poll_tag2(p + 128 * k, u[k], par); s0 += v.x; s1 += v.y; }
      sts_f2(sb + SM_CS1 + 8 * t, s0, s1);
    }
    __syncwarp();
    if (lane == 0) mbar_arrive(bar + 8 * B_CS1);
  }
  if ((wg >> 1) == rank) ffn<128, 128>(sb, g, j, out PROF_ARG);
  else if (rank) ffn<64, 128>(sb, g, j, out PROF_ARG);
  else ffn<128, 64>(sb, g, j, out PROF_ARG);
}

__global__ void __cluster_dims__(2, 1, 1) __launch_bounds__(NTHREADS, 1)
fused_block_kernel(const __grid_constant__ CUtensorMap tmX, const __grid_constant__ CUtensorMap tmWq, const __grid_constant__ CUtensorMap tmO,
                   const __grid_constant__ CUtensorMap tmWo, const __grid_constant__ CUtensorMap tmW1, const __grid_constant__ CUtensorMap tmW2,
                   const __nv_bfloat16* __restrict__ x, const __nv_bfloat16* __restrict__ wqkv, const __nv_bfloat16* __restrict__ wo,
                   const __nv_bfloat16* __restrict__ w1, const __nv_bfloat16* __restrict__ w2, __nv_bfloat16* __restrict__ out) {
  extern __shared__ __align__(1024) unsigned char smem[];
  const uint32_t sb = (uint32_t)__cvta_generic_to_shared(smem);
  const uint32_t bar = sb + SM_BAR;
  const int tid = threadIdx.x, warp = tid >> 5, lane = tid & 31;
  const int b = blockIdx.x, rank = b & 1;
  const int h = b & 15, r = b >> 4, g = b >> 3, j = b & 7;
  const int odd = h & 1, wcol0 = 28 * h - 4 * odd;
  uint32_t ep;
  asm volatile("ld.relaxed.gpu.global.u32 %0, [%1];" : "=r"(ep) : "l"(g_epoch + b) : "memory");

  if (warp >= 16) {
    asm volatile("setmaxnreg.dec.sync.aligned.u32 32;");
    if (warp > 16) return;
    if (lane == 0) {
      for (int i = 0; i < B_COUNT; i++) {
        int cnt = 1;
        if (i >= B_XREL && i < B_XREL + 3) cnt = 32;
        else if (i == B_XREL + 3 || i == B_KVFULL || (i >= B_KVREL && i < B_KVREL + 8) || i == B_AFREE2 || i == B_AFREE3_L || i == B_AFREE3_R) cnt = 16;
        else if (i == B_AFREE1) cnt = 32;
        else if (i == B_WODONE || i == B_GFREE_R || (i >= B_WREL && i < B_WREL + 28)) cnt = 8;
        else if (i == B_HFULL + j && j < 7) cnt = 2;
        else if (i >= B_GFULL && i < B_GFULL + 7 && ((i - B_GFULL >= 4) == (rank == 1))) cnt = 2;
        else if (i == B_CS1) cnt = 4;
        mbar_init(bar + 8 * i, cnt);
      }
      asm volatile("fence.mbarrier_init.release.cluster;" ::: "memory");
      fence_async_smem();
      for (int c = 0; c < 7; c++) {
        mbar_expect(bar + 8 * (B_XFULL + c), 32768 + 12288);
        tma3d(sb + SM_W + c * 12288, &tmWq, wcol0, 64 * c, 0, bar + 8 * (B_XFULL + c));
      }
      asm volatile("prefetch.tensormap [%0];" ::"l"(&tmX) : "memory");
    }
    __syncwarp();
    asm volatile("barrier.cluster.arrive.release.aligned;\nbarrier.cluster.wait.acquire.aligned;" ::: "memory");
    ep += 1;
    const uint32_t par = ep & 1;
    if (lane == 0) {
      for (int c = 0; c < 4; c++) tma2d_mc(sb + c * 32768 + rank * 16384, &tmX, 64 * c, 256 * r + 128 * rank, bar + 8 * (B_XFULL + c));
      for (int c = 4; c < 7; c++)
        asm volatile("cp.async.bulk.prefetch.tensor.2d.L2.global [%0, {%1, %2}];" ::"l"(&tmX), "r"(64 * c), "r"(256 * r + 128 * rank) : "memory");
      for (int k = 0; k < 7; k++)
        if ((k >= 4) != (rank == 1)) mbar_expect(bar + 8 * (B_GFULL + k), 16384);
      asm volatile("prefetch.tensormap [%0];" ::"l"(&tmO) : "memory");
      asm volatile("prefetch.tensormap [%0];" ::"l"(&tmWo) : "memory");
      asm volatile("prefetch.tensormap [%0];" ::"l"(&tmW1) : "memory");
      asm volatile("prefetch.tensormap [%0];" ::"l"(&tmW2) : "memory");
      for (int c = 4; c < 7; c++) {
        mbar_wait(bar + 8 * (B_XREL + c - 4));
        tma2d_mc(sb + (c - 4) * 32768 + rank * 16384, &tmX, 64 * c, 256 * r + 128 * rank, bar + 8 * (B_XFULL + c));
      }
    }
    __syncwarp();
    {
      for (int cp = lane; cp < 48; cp += 32) {
        const uint2* p = g_cs0 + h * 8 * 48 + cp;
        uint2 u[8];
#pragma unroll
        for (int k = 0; k < 8; k++) u[k] = ld_rlx2(p + 48 * k);
        float s0 = 0.f, s1 = 0.f;
#pragma unroll
        for (int k = 0; k < 8; k++) { const float2 v = poll_tag2(p + 48 * k, u[k], par); s0 += v.x; s1 += v.y; }
        sts_f2(sb + SM_CS0 + 8 * cp, s0, s1);
      }
      __syncwarp();
      if (lane == 0) mbar_arrive(bar + 8 * B_CS0);
    }
    const int w1c0 = 448 * (j >> 1) + 256 * rank;
    auto load_stage = [&](int s) {
      const uint32_t dst = sb + wslot(s), fb = bar + 8 * (B_WFULL + s);
      if (s < 14) {
        const int pair = s >= 7, na = (pair || !rank) ? 2 : 1;
        const int col = w1c0 + (pair ? (rank ? 64 : 128) : 0), row = 64 * hchunk(j, s - 7 * pair);
        mbar_expect(fb, na * 8192);
        for (int a = 0; a < na; a++) tma2d(dst + a * 8192, &tmW1, col + 64 * a, row, fb);
      } else {
        const int pair = s < 20 ? (s >= 17) : ((s >> 1) & 1);
        const int t = s < 20 ? s - 14 - 3 * pair : s < 24 ? s - 17 - 2 * pair : s - 19 - 2 * pair;
        const int na = (!pair || rank) ? 2 : 1;
        const int col = 64 * (rank ? 3 + 2 * pair : 2 * pair), row = 448 * (j >> 1) + 64 * gchunk(rank, t);
        mbar_expect(fb, na * 8192);
        for (int a = 0; a < na; a++) tma2d(dst + a * 8192, &tmW2, col + 64 * a, row, fb);
      }
    };
    if (lane == 0) {
      mbar_wait(bar + 8 * B_KVFULL);
      bulk_s2g(g_kv + (size_t)(h * 8 + r) * 32768, sb + SM_KV0, 32768);
      bulk_s2g(g_kvtr + (h * 8 + r) * 4, sb + SM_TR, 16);
      bulk_commit_wait();
      fence_async_all();
      fence_gpu();
      asm volatile("st.relaxed.gpu.global.u32 [%0], %1;" ::"l"(g_flagKV + (h * 8 + r) * 8), "r"(ep) : "memory");
      PMARK(4, 1);
      for (int blk = 1; blk < 8; blk++) {
        const int pr = (r + blk) & 7;
        if (blk >= 4) mbar_wait(bar + 8 * (B_KVREL + blk - 3));
        wait_count(g_flagKV + (h * 8 + pr) * 8, ep);
        fence_async_all();
        const uint32_t fb = bar + 8 * (B_KVFULL + blk);
        mbar_expect(fb, 32768 + 16);
        bulk_g2s(sb + ((blk - 1) % 3) * 32768, g_kv + (size_t)(h * 8 + pr) * 32768, 32768, fb);
        bulk_g2s(sb + SM_TR + 16 * blk, g_kvtr + (h * 8 + pr) * 4, 16, fb);
        if (blk == 3) {
          PMARK(4, 2);
          l2_prefetch((const char*)wo + b * 3136, 3136);
          l2_prefetch((const char*)w1 + b * 12544, 12544);
          l2_prefetch((const char*)w2 + b * 12544, 12544);
        }
        if (blk == 5) {
          mbar_wait(bar + 8 * B_KVREL);
          if (j < 7) {
            mbar_expect(bar + 8 * B_WOFULL, 7 * 8192);
            for (int c = 0; c < 7; c++) tma2d(sb + SM_G + c * 8192, &tmWo, 64 * j, 64 * c, bar + 8 * B_WOFULL);
          }
          for (int s = 0; s < 3; s++) load_stage(s);
        }
      }
      for (int c = 0; c < 7; c++) mbar_expect(bar + 8 * (B_OFULL + c), 16384);
      for (int c = 0; c < 7; c++)
        if (c != j) mbar_expect(bar + 8 * (B_HFULL + c), 16384);
      mbar_wait(bar + 8 * B_AFREE1);
      PMARK(4, 3);
      wait_count(g_cntO + g * 8, 32 * ep);
      fence_async_all();
      PMARK(4, 4);
      for (int c = 0; c < 7; c++) tma2d_mc(sb + SM_A + c * 16384 + rank * 8192, &tmO, 64 * c, 128 * g + 64 * rank, bar + 8 * (B_OFULL + c));
      mbar_wait(bar + 8 * B_WODONE);
      for (int s = 3; s < 6; s++) load_stage(s);
      mbar_wait(bar + 8 * B_AFREE2);
      PMARK(4, 5);
    }
    __syncwarp();
    {
      bool done = lane >= 7 || lane == j;
      uint32_t t0 = 0;
      while (true) {
        if (!done && (int)(ld_acquire(g_flagH + (g * 8 + lane) * 8) - 2 * ep) >= 0) {
          fence_async_all();
          const unsigned char* src = g_h + (size_t)(g * 7 + lane) * 16384;
          const uint32_t dst = sb + SM_A + lane * 16384, fb = bar + 8 * (B_HFULL + lane);
          if (lane == (j ^ 1)) bulk_g2s(dst, src, 16384, fb);
          else bulk_g2s_mc(dst + rank * 8192, src + rank * 8192, 8192, fb);
          done = true;
        }
        if (__all_sync(0xffffffffu, done || timed_out(t0))) break;
      }
    }
    if (lane == 0) {
      PMARK(4, 6);
      for (int s = 6; s < 28; s++) {
        const int dep = s < 9 ? s - 6 : s < 17 ? s - 3 : s < 20 ? -1 : s - 6;
        mbar_wait(bar + 8 * (dep >= 0 ? B_WREL + dep : B_AFREE3_L));
        load_stage(s);
      }
      PMARK(4, 7);
      g_epoch[b] = ep;
    }
    __syncwarp();
    asm volatile("barrier.cluster.arrive.release.aligned;\nbarrier.cluster.wait.acquire.aligned;" ::: "memory");
    return;
  }

  asm volatile("setmaxnreg.inc.sync.aligned.u32 112;");
  const int wg = warp >> 2, warp4 = warp & 3, c4 = lane & 3;
  if (tid < 4) asm volatile("st.shared.u32 [%0], %1;" ::"r"(sb + SM_TR + 4 * tid), "r"(0) : "memory");
  asm volatile("barrier.cluster.arrive.release.aligned;" ::: "memory");
  {
    const int srow = 256 * r + 16 * h + warp;
    uint4 xa = make_uint4(0, 0, 0, 0), xb = xa;
    if (lane < 28) {
      const uint4* xp = reinterpret_cast<const uint4*>(x + (size_t)srow * ND);
      xa = __ldg(xp + lane);
      xb = __ldg(xp + lane + 28);
    }
    uint32_t wv[7];
    const int cp = tid % 48, rg = tid / 48;
    if (tid < 384) {
      const __nv_bfloat16* wp = wqkv + (size_t)(56 * r + 7 * rg) * (3 * ND) + (cp >> 4) * ND + wcol0 + 2 * (cp & 15);
#pragma unroll
      for (int k = 0; k < 7; k++) wv[k] = __ldg(reinterpret_cast<const uint32_t*>(wp + k * 3 * ND));
    }
    asm volatile("barrier.cluster.wait.acquire.aligned;" ::: "memory");
    ep += 1;
    const uint32_t xs[8] = {xa.x, xa.y, xa.z, xa.w, xb.x, xb.y, xb.z, xb.w};
    float s = 0.f;
#pragma unroll
    for (int k = 0; k < 8; k++) s += b_lo(xs[k]) + b_hi(xs[k]);
#pragma unroll
    for (int o = 16; o; o >>= 1) s += __shfl_xor_sync(0xffffffffu, s, o);
    const float mu = s * (1.f / ND);
    float v = 0.f;
#pragma unroll
    for (int k = 0; k < 8; k++) { const float d0 = b_lo(xs[k]) - mu, d1 = b_hi(xs[k]) - mu; v += d0 * d0 + d1 * d1; }
    if (lane >= 28) v = 0.f;
#pragma unroll
    for (int o = 16; o; o >>= 1) v += __shfl_xor_sync(0xffffffffu, v, o);
    if (lane == 0) st_tag2(g_st1 + srow, mu, 1.f / sqrtf(v * (1.f / ND) + 1e-5f), ep & 1);
    if (tid < 384) {
      float s0 = 0.f, s1 = 0.f;
#pragma unroll
      for (int k = 0; k < 7; k++) { s0 += b_lo(wv[k]); s1 += b_hi(wv[k]); }
      sts_f2(sb + SM_RED + (rg * 48 + cp) * 8, s0, s1);
    }
    if (tid == 0) sts_u32(sb + SM_EP, ep);
    bar_sync(1, 512);
    if (tid < 48) {
      float s0 = 0.f, s1 = 0.f;
#pragma unroll
      for (int k = 0; k < 8; k++) { const float2 t = lds_f2(sb + SM_RED + (k * 48 + tid) * 8); s0 += t.x; s1 += t.y; }
      st_tag2(g_cs0 + (h * 8 + r) * 48 + tid, s0, s1, ep & 1);
    }
  }
  const uint32_t par = ep & 1;
  PMARK(wg, 0);
  const int row0 = 256 * r + 64 * wg + 16 * warp4 + (lane >> 2);
  uint32_t q[8];
  {
    float acc[48];
#pragma unroll
    for (int c = 0; c < 7; c++) {
      mbar_wait(bar + 8 * (B_XFULL + c));
      if (c == 0) PMARK(wg, 1);
      const uint64_t da = mkdesc(sb + (c & 3) * 32768 + wg * 8192, 16, 1024, 1);
      const uint64_t db = mkdesc(sb + SM_W + c * 12288, 4096, 512, 2);
      wg_fence();
#pragma unroll
      for (int k = 0; k < 4; k++) mma_ss_n96_bf16_f32(acc, dadd(da, 32 * k), dadd(db, 1024 * k), (c | k) != 0);
      wg_commit();
      if (c >= 1 && c <= 4) {
        wg_wait<1>();
        if (lane == 0) {
          mbar_arrive(bar + 8 * (B_XREL + c - 1));
          if (c < 4) mbar_arrive_remote(mapa(bar + 8 * (B_XREL + c - 1), rank ^ 1));
        }
      }
    }
    const uint2 u0 = ld_rlx2(g_st1 + row0), u1 = ld_rlx2(g_st1 + row0 + 8);
    wg_wait<0>();
    pin(acc);
    PMARK(wg, 2);
    const float2 s0 = poll_tag2(g_st1 + row0, u0, par), s1 = poll_tag2(g_st1 + row0 + 8, u1, par);
    mbar_wait(bar + 8 * B_CS0);
    mbar_wait(bar + 8 * (B_XREL + 3));
    const bool padA = odd && c4 < 2, padB = !odd && c4 >= 2;
    uint32_t pk[24];
    float n0[2] = {0.f, 0.f}, n1[2] = {0.f, 0.f}, vm = 0.f;
#pragma unroll
    for (int n = 0; n < 12; n++) {
      const float2 cs = lds_f2(sb + SM_CS0 + 32 * n + 8 * c4);
      const float sc = n < 4 ? 0.27264365f : 1.f;
      float z0 = fmaf(-s0.x, cs.x, acc[4 * n]) * (s0.y * sc), z1 = fmaf(-s0.x, cs.y, acc[4 * n + 1]) * (s0.y * sc);
      float z2 = fmaf(-s1.x, cs.x, acc[4 * n + 2]) * (s1.y * sc), z3 = fmaf(-s1.x, cs.y, acc[4 * n + 3]) * (s1.y * sc);
      if (((n & 3) == 0 && padA) || ((n & 3) == 3 && padB)) z0 = z1 = z2 = z3 = 0.f;
      if (n < 8) {
        n0[n >> 2] += z0 * z0 + z1 * z1;
        n1[n >> 2] += z2 * z2 + z3 * z3;
      } else {
        vm = fmaxf(fmaxf(vm, fmaxf(fabsf(z0), fabsf(z1))), fmaxf(fabsf(z2), fabsf(z3)));
        if ((n == 8 && odd && c4 == 0) || (n == 11 && !odd && c4 == 2)) z0 = z2 = 1.f;
      }
      pk[2 * n] = pack_h2(z0, z1);
      pk[2 * n + 1] = pack_h2(z2, z3);
    }
    const int srow = 64 * wg + 16 * warp4 + (lane & 7) + 8 * ((lane >> 3) & 1);
    const uint32_t sa = sb + SM_KV0 + srow * 64;
    const uint32_t x0 = ((lane >> 4) ^ ((srow >> 1) & 3)) << 4;
#pragma unroll
    for (int i = 0; i < 8; i++) q[i] = pk[i];
    stsm4(sa + x0, pk[8], pk[9], pk[10], pk[11]);
    stsm4(sa + (x0 ^ 32), pk[12], pk[13], pk[14], pk[15]);
    stsm4(sa + 16384 + x0, pk[16], pk[17], pk[18], pk[19]);
    stsm4(sa + 16384 + (x0 ^ 32), pk[20], pk[21], pk[22], pk[23]);
    const int qa = __float_as_int(quad_sum(n0[0])), qb = __float_as_int(quad_sum(n1[0]));
    sts_u32(sb + SM_RED + 4 * tid, max(qa & 0x7fffffff, qb & 0x7fffffff));
    const int ka = __float_as_int(quad_sum(n0[1])), kb = __float_as_int(quad_sum(n1[1]));
    const int km = __reduce_max_sync(0xffffffffu, max(ka & 0x7fffffff, kb & 0x7fffffff));
    const int vmx = __reduce_max_sync(0xffffffffu, __float_as_int(vm));
    if (lane == 0) {
      asm volatile("red.shared.max.s32 [%0], %1;" ::"r"(sb + SM_TR), "r"(km) : "memory");
      asm volatile("red.shared.max.s32 [%0], %1;" ::"r"(sb + SM_TR + 4), "r"(vmx) : "memory");
    }
    fence_async_smem();
    __syncwarp();
    if (lane == 0) mbar_arrive(bar + 8 * B_KVFULL);
  }
  PMARK(wg, 3);
  {
    float o[16];
    uint32_t sc[32], oh[8];
#pragma unroll
    for (int i = 0; i < 16; i++) o[i] = 0.f;
    uint64_t kd = mkdesc(sb + SM_KV0, 16, 512, 2);
    mbar_wait(bar + 8 * B_KVFULL);
    pin(q);
    wg_fence();
    mma_rs_n128_f16_f16<0>(sc, q[0], q[1], q[2], q[3], kd);
    mma_rs_n128_f16_f16<1>(sc, q[4], q[5], q[6], q[7], dadd(kd, 32));
    wg_commit();
    wg_wait<0>();
    pin(sc);
    PMARK(wg, 4);
    uint32_t nslot = 0;
#pragma unroll 1
    for (int blk = 0; blk < 8; blk++) {
      attn_tile<1>(sc, oh, q, dadd(kd, 8192), dadd(kd, 16384));
      uint64_t kn = kd;
      if (blk < 7) {
        mbar_wait(bar + 8 * (B_KVFULL + 1 + blk));
        kn = mkdesc(sb + nslot, 16, 512, 2);
        nslot = nslot == 65536 ? 0 : nslot + 32768;
      }
      attn_tile<0>(sc, oh, q, kn, dadd(kd, 16384 + 8192));
      if ((fresh_tid() & 31) == 0) mbar_arrive(bar + 8 * (B_KVREL + blk));
#pragma unroll
      for (int i = 0; i < 8; i++) {
        const float2 f = __half22float2(*reinterpret_cast<const __half2*>(&oh[i]));
        o[2 * i] += f.x;
        o[2 * i + 1] += f.y;
      }
      kd = kn;
    }
    const int tid = fresh_tid(), lane = tid & 31, wg = tid >> 7, warp4 = (tid >> 5) & 3, c4 = lane & 3;
    const int row0 = 256 * r + 64 * wg + 16 * warp4 + (lane >> 2);
    const float qn2 = __uint_as_float(lds_u32(sb + SM_RED + 4 * tid));
    PMARK(wg, 5);
    if (lane == 0) {
      mbar_arrive(bar + 8 * B_AFREE1);
      mbar_arrive_remote(mapa(bar + 8 * B_AFREE1, rank ^ 1));
    }
    const int src = (lane & 28) | (odd ? 0 : 2);
    const float l0 = __shfl_sync(0xffffffffu, odd ? o[0] : o[12], src), l1 = __shfl_sync(0xffffffffu, odd ? o[2] : o[14], src);
    const float2 tr = lds_f2(sb + SM_TR + 16 * (lane & 7));
    const float kn2 = __int_as_float(__reduce_max_sync(0xffffffffu, __float_as_int(tr.x)));
    const float vmx = __int_as_float(__reduce_max_sync(0xffffffffu, __float_as_int(tr.y)));
    float om = 0.f;
#pragma unroll
    for (int i = 0; i < 16; i++) om += fabsf(o[i]);
    const float lm = fminf(l0, l1);
    const bool ok = qn2 * kn2 <= 950.f && qn2 <= 1e6f && kn2 <= 1e6f && vmx <= 3e4f && vmx >= 2.5e-4f && om <= 1e30f &&
                    l0 <= 1e30f && l1 <= 1e30f && lm >= 0.03125f && lm * vmx >= 0.00390625f;
    if (__all_sync(0xffffffffu, ok)) {
      const float i0 = 1.f / l0, i1 = 1.f / l1;
      __nv_bfloat16* op = g_O + (size_t)row0 * ND + wcol0 + 2 * c4;
#pragma unroll
      for (int n = 0; n < 4; n++) {
        if ((n == 0 && odd && c4 < 2) || (n == 3 && !odd && c4 >= 2)) continue;
        *reinterpret_cast<uint32_t*>(op + 8 * n) = pack_b2(o[4 * n] * i0, o[4 * n + 1] * i0);
        *reinterpret_cast<uint32_t*>(op + 8 * ND + 8 * n) = pack_b2(o[4 * n + 2] * i1, o[4 * n + 3] * i1);
      }
    } else {
      attention_exact(x, wqkv, h, 256 * r + 64 * wg + 16 * warp4);
    }
    bar_sync(2 + wg, 128);
    if (warp4 == 0 && lane == 0) {
      fence_gpu();
      red_add(g_cntO + (2 * r + (wg >> 1)) * 8);
    }
    PMARK(wg, 6);
  }
  phase_c(sb, g, j, x, w1, out PROF_ARG);
  asm volatile("barrier.cluster.wait.acquire.aligned;" ::: "memory");
}

typedef CUresult (*EncodeFn)(CUtensorMap*, CUtensorMapDataType, cuuint32_t, void*, const cuuint64_t*, const cuuint64_t*, const cuuint32_t*,
                             const cuuint32_t*, CUtensorMapInterleave, CUtensorMapSwizzle, CUtensorMapL2promotion, CUtensorMapFloatOOBfill);

void make2d(EncodeFn enc, CUtensorMap* tm, const void* p, int rows, int cols, int box_rows) {
  cuuint64_t dims[2] = {(cuuint64_t)cols, (cuuint64_t)rows}, str[1] = {(cuuint64_t)cols * 2};
  cuuint32_t box[2] = {64, (cuuint32_t)box_rows}, es[2] = {1, 1};
  enc(tm, CU_TENSOR_MAP_DATA_TYPE_BFLOAT16, 2, const_cast<void*>(p), dims, str, box, es, CU_TENSOR_MAP_INTERLEAVE_NONE,
      CU_TENSOR_MAP_SWIZZLE_128B, CU_TENSOR_MAP_L2_PROMOTION_L2_128B, CU_TENSOR_MAP_FLOAT_OOB_FILL_NONE);
}

}

extern "C" void kernel_launch(void* const* d_in, const int* in_sizes, int n_in, void* d_out, int out_size) {
  const __nv_bfloat16* x = (const __nv_bfloat16*)d_in[0];
  const __nv_bfloat16* wqkv = (const __nv_bfloat16*)d_in[1];
  const __nv_bfloat16* wo = (const __nv_bfloat16*)d_in[2];
  const __nv_bfloat16* w1 = (const __nv_bfloat16*)d_in[4];
  const __nv_bfloat16* w2 = (const __nv_bfloat16*)d_in[5];
  void* fn = nullptr;
  cudaDriverEntryPointQueryResult qr;
  cudaGetDriverEntryPoint("cuTensorMapEncodeTiled", &fn, cudaEnableDefault, &qr);
  EncodeFn enc = (EncodeFn)fn;
  void* optr = nullptr;
  cudaGetSymbolAddress(&optr, g_O);
  CUtensorMap tmX, tmWq, tmO, tmWo, tmW1, tmW2;
  make2d(enc, &tmX, x, NS, ND, 128);
  make2d(enc, &tmO, optr, NS, ND, 64);
  make2d(enc, &tmWo, wo, ND, ND, 64);
  make2d(enc, &tmW1, w1, ND, NF, 64);
  make2d(enc, &tmW2, w2, NF, ND, 64);
  {
    cuuint64_t dims[3] = {ND, ND, 3}, str[2] = {3 * ND * 2, ND * 2};
    cuuint32_t box[3] = {32, 64, 3}, es[3] = {1, 1, 1};
    enc(&tmWq, CU_TENSOR_MAP_DATA_TYPE_BFLOAT16, 3, const_cast<__nv_bfloat16*>(wqkv), dims, str, box, es, CU_TENSOR_MAP_INTERLEAVE_NONE,
        CU_TENSOR_MAP_SWIZZLE_64B, CU_TENSOR_MAP_L2_PROMOTION_L2_128B, CU_TENSOR_MAP_FLOAT_OOB_FILL_NONE);
  }
  cudaFuncSetAttribute(fused_block_kernel, cudaFuncAttributeMaxDynamicSharedMemorySize, SM_TOTAL);
  fused_block_kernel<<<128, NTHREADS, SM_TOTAL, cudaStreamPerThread>>>(tmX, tmWq, tmO, tmWo, tmW1, tmW2, x, wqkv, wo, w1, w2,
                                                                         (__nv_bfloat16*)d_out);
}
```

```cpp
#include <cuda_runtime.h>
#include <cuda.h>
#include <cuda_bf16.h>
#include <cuda_fp16.h>
#include <stdint.h>

namespace {

constexpr int NS = 2048, ND = 448, NF = 1792;
constexpr int NTHREADS = 640;
#define POLY_MASK 0x56B5AD5Au
#define POLY_DEG 2

constexpr uint32_t SM_A = 0;
constexpr uint32_t SM_G = 114688;
constexpr uint32_t SM_R = 172032;
constexpr uint32_t SM_W = 131072;
constexpr uint32_t SM_KV0 = 98304;
constexpr uint32_t SM_BAR = 221184;
constexpr uint32_t SM_TR = SM_BAR + 1088;
constexpr uint32_t SM_CS0 = SM_TR + 128;
constexpr uint32_t SM_CS1 = SM_CS0 + 384;
constexpr uint32_t SM_RED = SM_CS1 + 1024;
constexpr uint32_t SM_ZERO = SM_RED + 3072;
constexpr uint32_t SM_EP = SM_ZERO + 2048;
constexpr uint32_t SM_PROF = SM_EP + 32;
constexpr uint32_t SM_TOTAL = SM_PROF + 1024 + 384;

enum : int {
  B_XFULL = 0, B_WQ = 7, B_XREL = 14, B_ST = 18, B_STDONE = 19, B_CS0 = 20, B_KVFULL = 21  , B_KVREL = 37, B_AFREE1 = 45,
  B_OFULL = 46, B_WOFULL = 54, B_AFREE2 = 55, B_WODONE = 56, B_HFULL = 57, B_WFULL = 64, B_WREL = 92, B_GFULL = 120,
  B_AFREE3_L = 127, B_AFREE3_R = 128, B_CS1 = 129, B_COUNT = 130
};

__device__ uint4 g_epoch[128];
__device__ __align__(128) unsigned char g_kv[16 * 8 * 32896];
__device__ uint32_t g_flagKV[16 * 8 * 8];
__device__ __align__(128) unsigned char g_O[16 * 16 * 8192];
__device__ uint32_t g_flagO[16 * 8 * 8];
__device__ __align__(128) unsigned char g_h[16 * 7 * 16384];
__device__ uint32_t g_flagH[16 * 8 * 8];
__device__ uint2 g_st1[NS];
__device__ uint4 g_cs0[16 * 8 * 24];
__device__ uint2 g_st2[7 * NS];
__device__ uint2 g_cs1[8 * 16 * 128];
__device__ uint4 g_part[16 * 2 * 4 * 4 * 4 * 2 * 128];
#define PMARK(role, i) do {} while (0)
#define PDUMP(role) do {} while (0)
#define PSTAGE(k, s) do {} while (0)
#define PROF_PARAM
#define PROF_ARG

__device__ __forceinline__ void wg_fence() { asm volatile("wgmma.fence.sync.aligned;" ::: "memory"); }
__device__ __forceinline__ void wg_commit() { asm volatile("wgmma.commit_group.sync.aligned;" ::: "memory"); }
template <int N> __device__ __forceinline__ void wg_wait() { asm volatile("wgmma.wait_group.sync.aligned %0;" ::"n"(N) : "memory"); }
template <int N> __device__ __forceinline__ void pin(float (&d)[N]) {
#pragma unroll
  for (int i = 0; i < N; i++) asm volatile("" : "+f"(d[i])::"memory");
}
template <int N> __device__ __forceinline__ void pin(uint32_t (&d)[N]) {
#pragma unroll
  for (int i = 0; i < N; i++) asm volatile("" : "+r"(d[i])::"memory");
}
__device__ __forceinline__ uint64_t mkdesc(uint32_t addr, uint32_t lbo, uint32_t sbo, uint32_t sw) {
  return ((uint64_t)((sbo >> 4) | (sw << 30)) << 32) | (uint64_t)(((addr & 0x3FFFFu) >> 4) | ((lbo >> 4) << 16));
}
__device__ __forceinline__ uint64_t dadd(uint64_t d, uint32_t off) {
  return (d & 0xFFFFFFFF00000000ull) | (uint32_t)((uint32_t)d + (off >> 4));
}
__device__ __forceinline__ bool timed_out(uint32_t sb) {
  uint32_t t0, t;
  asm volatile("ld.shared.u32 %0, [%1];" : "=r"(t0) : "r"(sb + SM_EP + 16));
  asm volatile("mov.u32 %0, %%clock;" : "=r"(t));
  return (int)(t - t0) < 0;
}
__device__ __forceinline__ void mbar_init(uint32_t b, uint32_t cnt) { asm volatile("mbarrier.init.shared::cta.b64 [%0], %1;" ::"r"(b), "r"(cnt) : "memory"); }
__device__ __forceinline__ uint32_t bar_count(int i, int j, int rank) {
  if (i >= B_XREL && i < B_XREL + 3) return 32;
  if (i == B_AFREE1) return 42;
  if (i == B_XREL + 3 || i == B_STDONE || (i >= B_KVREL && i < B_KVREL + 8) || i == B_AFREE2 || i == B_AFREE3_L || i == B_AFREE3_R) return 16;
  if (i == B_WODONE || i == B_KVFULL || i == B_KVFULL + 1 || (i >= B_WREL && i < B_WREL + 28)) return 8;
  if (i == B_HFULL + j && j < 7) return 2;
  if (i == B_CS1) return 4;
  if (i >= B_GFULL && i < B_GFULL + 7 && ((i - B_GFULL >= 4) == (rank == 1))) return 8;
  return 1;
}
__device__ __forceinline__ void mbar_expect(uint32_t b, uint32_t bytes) {
  asm volatile("mbarrier.arrive.expect_tx.shared::cta.b64 _, [%0], %1;" ::"r"(b), "r"(bytes) : "memory");
}
__device__ __forceinline__ void mbar_arrive(uint32_t b) { asm volatile("mbarrier.arrive.shared::cta.b64 _, [%0];" ::"r"(b) : "memory"); }
__device__ __forceinline__ uint32_t mapa(uint32_t a, uint32_t rank) {
  uint32_t r;
  asm("mapa.shared::cluster.u32 %0, %1, %2;" : "=r"(r) : "r"(a), "r"(rank));
  return r;
}
__device__ __forceinline__ void mbar_arrive_remote(uint32_t rb) {
  asm volatile("mbarrier.arrive.shared::cluster.b64 _, [%0];" ::"r"(rb) : "memory");
}
__device__ __forceinline__ void mbar_wait_addr(uint32_t sb, uint32_t addr) {
  asm volatile(
      "{\n.reg .pred p;\n.reg .u32 t0, t1;\n"
      "W_LOOP:\n"
      "mbarrier.try_wait.parity.shared::cta.b64 p, [%0], 0, 20000;\n"
      "@p bra W_DONE;\n"
      "ld.shared.u32 t0, [%1];\nmov.u32 t1, %%clock;\nsub.u32 t1, t1, t0;\nsetp.ge.s32 p, t1, 0;\n"
      "@p bra W_LOOP;\n"
      "W_DONE:\n}"
      ::"r"(addr), "r"(sb + SM_EP + 16) : "memory");
}
__device__ __forceinline__ uint32_t mbar_test(uint32_t sb, int idx) {
  uint32_t ok;
  asm volatile("{\n.reg .pred p;\nmbarrier.test_wait.parity.shared::cta.b64 p, [%1], 0;\nselp.u32 %0, 1, 0, p;\n}"
               : "=r"(ok) : "r"(sb + SM_BAR + 8 * idx) : "memory");
  return ok;
}
__device__ __forceinline__ void mbar_wait(uint32_t sb, int idx) { mbar_wait_addr(sb, sb + SM_BAR + 8 * idx); }
__device__ __forceinline__ void bar_sync(int id, int n) { asm volatile("bar.sync %0, %1;" ::"r"(id), "r"(n) : "memory"); }
__device__ __forceinline__ void fence_async_smem() { asm volatile("fence.proxy.async.shared::cta;" ::: "memory"); }
__device__ __forceinline__ void fence_async_all() { asm volatile("fence.proxy.async.global;" ::: "memory"); }
__device__ __forceinline__ void tma2d(uint32_t dst, const CUtensorMap* tm, int c0, int c1, uint32_t bar) {
  asm volatile("cp.async.bulk.tensor.2d.shared::cluster.global.mbarrier::complete_tx::bytes [%0], [%1, {%3, %4}], [%2];"
               ::"r"(dst), "l"(tm), "r"(bar), "r"(c0), "r"(c1) : "memory");
}
__device__ __forceinline__ void tma2d_mc(uint32_t dst, const CUtensorMap* tm, int c0, int c1, uint32_t bar) {
  asm volatile("cp.async.bulk.tensor.2d.shared::cluster.global.mbarrier::complete_tx::bytes.multicast::cluster [%0], [%1, {%3, %4}], [%2], %5;"
               ::"r"(dst), "l"(tm), "r"(bar), "r"(c0), "r"(c1), "h"((uint16_t)3) : "memory");
}
__device__ __forceinline__ void tma3d(uint32_t dst, const CUtensorMap* tm, int c0, int c1, int c2, uint32_t bar) {
  asm volatile("cp.async.bulk.tensor.3d.shared::cluster.global.mbarrier::complete_tx::bytes [%0], [%1, {%3, %4, %5}], [%2];"
               ::"r"(dst), "l"(tm), "r"(bar), "r"(c0), "r"(c1), "r"(c2) : "memory");
}
__device__ __forceinline__ void bulk_g2s(uint32_t dst, const void* src, uint32_t bytes, uint32_t bar) {
  asm volatile("cp.async.bulk.shared::cluster.global.mbarrier::complete_tx::bytes [%0], [%1], %2, [%3];"
               ::"r"(dst), "l"(src), "r"(bytes), "r"(bar) : "memory");
}
__device__ __forceinline__ void bulk_g2s_mc(uint32_t dst, const void* src, uint32_t bytes, uint32_t bar) {
  asm volatile("cp.async.bulk.shared::cluster.global.mbarrier::complete_tx::bytes.multicast::cluster [%0], [%1], %2, [%3], %4;"
               ::"r"(dst), "l"(src), "r"(bytes), "r"(bar), "h"((uint16_t)3) : "memory");
}
__device__ __forceinline__ void bulk_s2g(void* dst, uint32_t src, uint32_t bytes) {
  asm volatile("cp.async.bulk.global.shared::cta.bulk_group [%0], [%1], %2;" ::"l"(dst), "r"(src), "r"(bytes) : "memory");
}
__device__ __forceinline__ void bulk_s2peer(uint32_t rdst, uint32_t src, uint32_t bytes, uint32_t rbar) {
  asm volatile("cp.async.bulk.shared::cluster.shared::cta.mbarrier::complete_tx::bytes [%0], [%1], %2, [%3];"
               ::"r"(rdst), "r"(src), "r"(bytes), "r"(rbar) : "memory");
}
__device__ __forceinline__ void bulk_commit_wait() {
  asm volatile("cp.async.bulk.commit_group;\ncp.async.bulk.wait_group 0;" ::: "memory");
}
__device__ __forceinline__ void l2_prefetch(const void* p, uint32_t bytes) {
  asm volatile("cp.async.bulk.prefetch.L2.global [%0], %1;" ::"l"(p), "r"(bytes) : "memory");
}
__device__ __forceinline__ uint32_t ld_acquire(const uint32_t* p) {
  uint32_t v;
  asm volatile("ld.acquire.gpu.global.u32 %0, [%1];" : "=r"(v) : "l"(p) : "memory");
  return v;
}
__device__ __forceinline__ void red_add(uint32_t* p) { asm volatile("red.relaxed.gpu.global.add.u32 [%0], 1;" ::"l"(p) : "memory"); }
__device__ __forceinline__ uint32_t tagw(float v, uint32_t par) { return (__float_as_uint(v) & ~1u) | par; }
__device__ __forceinline__ void st_tag2(uint2* p, float a, float b, uint32_t par) {
  asm volatile("st.relaxed.gpu.global.v2.u32 [%0], {%1, %2};" ::"l"(p), "r"(tagw(a, par)), "r"(tagw(b, par)) : "memory");
}
__device__ __forceinline__ uint2 ld_rlx2(const uint2* p) {
  uint2 v;
  asm volatile("ld.relaxed.gpu.global.v2.u32 {%0, %1}, [%2];" : "=r"(v.x), "=r"(v.y) : "l"(p) : "memory");
  return v;
}
__device__ __forceinline__ void st_rec(uint4* p, uint32_t a, uint32_t b, uint32_t c, uint32_t d) {
  asm volatile("{\n.reg .b128 v;\n.reg .b64 lo, hi;\nmov.b64 lo, {%1, %2};\nmov.b64 hi, {%3, %4};\nmov.b128 v, {lo, hi};\n"
               "st.relaxed.gpu.global.b128 [%0], v;\n}" ::"l"(p), "r"(a), "r"(b), "r"(c), "r"(d) : "memory");
}
__device__ __forceinline__ uint4 ld_rec(const uint4* p) {
  uint4 v;
  asm volatile("{\n.reg .b128 v;\n.reg .b64 lo, hi;\nld.relaxed.gpu.global.b128 v, [%4];\nmov.b128 {lo, hi}, v;\n"
               "mov.b64 {%0, %1}, lo;\nmov.b64 {%2, %3}, hi;\n}" : "=r"(v.x), "=r"(v.y), "=r"(v.z), "=r"(v.w) : "l"(p) : "memory");
  return v;
}
__device__ __forceinline__ uint32_t pack_h2(float lo, float hi) {
  uint32_t r;
  asm("cvt.rn.f16x2.f32 %0, %1, %2;" : "=r"(r) : "f"(hi), "f"(lo));
  return r;
}
__device__ __forceinline__ uint32_t pack_b2(float lo, float hi) {
  uint32_t r;
  asm("cvt.rn.bf16x2.f32 %0, %1, %2;" : "=r"(r) : "f"(hi), "f"(lo));
  return r;
}
__device__ __forceinline__ float b_lo(uint32_t v) { return __uint_as_float(v << 16); }
__device__ __forceinline__ float b_hi(uint32_t v) { return __uint_as_float(v & 0xFFFF0000u); }
__device__ __forceinline__ void stsm4(uint32_t addr, uint32_t a, uint32_t b, uint32_t c, uint32_t d) {
  asm volatile("stmatrix.sync.aligned.m8n8.x4.shared.b16 [%0], {%1, %2, %3, %4};" ::"r"(addr), "r"(a), "r"(b), "r"(c), "r"(d) : "memory");
}
__device__ __forceinline__ float2 lds_f2(uint32_t a) {
  float2 v;
  asm volatile("ld.shared.v2.f32 {%0, %1}, [%2];" : "=f"(v.x), "=f"(v.y) : "r"(a) : "memory");
  return v;
}
__device__ __forceinline__ uint32_t lds_u32(uint32_t a) {
  uint32_t v;
  asm volatile("ld.shared.u32 %0, [%1];" : "=r"(v) : "r"(a) : "memory");
  return v;
}
__device__ __forceinline__ uint32_t epoch(uint32_t sb) { return lds_u32(sb + SM_EP) + 1; }
__device__ __forceinline__ void sts_f2(uint32_t a, float x, float y) { asm volatile("st.shared.v2.f32 [%0], {%1, %2};" ::"r"(a), "f"(x), "f"(y) : "memory"); }
__device__ __forceinline__ float quad_sum(float v) {
  v += __shfl_xor_sync(0xffffffffu, v, 1);
  return v + __shfl_xor_sync(0xffffffffu, v, 2);
}

__device__ __forceinline__ int fresh_tid() {
  int t;
  asm volatile("mov.u32 %0, %%tid.x;" : "=r"(t));
  return t;
}
__device__ __forceinline__ int fresh_lane() {
  int t;
  asm volatile("mov.u32 %0, %%laneid;" : "=r"(t));
  return t;
}
__device__ __forceinline__ bool elect_one() {
  uint32_t p;
  asm volatile("{\n.reg .pred p;\nelect.sync _|p, 0xffffffff;\nselp.u32 %0, 1, 0, p;\n}" : "=r"(p));
  return p;
}
__device__ __forceinline__ void sts_u32(uint32_t a, uint32_t v) { asm volatile("st.shared.u32 [%0], %1;" ::"r"(a), "r"(v) : "memory"); }

__device__ __forceinline__ void mma_ss_n96_bf16_f32(float (&d)[48], uint64_t da, uint64_t db, int acc) {
  asm volatile(
      "{\n.reg .pred p;\nsetp.ne.b32 p, %50, 0;\n"
      "wgmma.mma_async.sync.aligned.m64n96k16.f32.bf16.bf16 {"
      "%0, %1, %2, %3, %4, %5, %6, %7, %8, %9, %10, %11, %12, %13, %14, %15, %16, %17, %18, %19, %20, %21, %22, "
      "%23, %24, %25, %26, %27, %28, %29, %30, %31, %32, %33, %34, %35, %36, %37, %38, %39, %40, %41, %42, %43, "
      "%44, %45, %46, %47"
      "}, %48, %49, p, 1, 1, 0, 1;\n}\n"
      : "+f"(d[0]), "+f"(d[1]), "+f"(d[2]), "+f"(d[3]), "+f"(d[4]), "+f"(d[5]), "+f"(d[6]), "+f"(d[7]),
        "+f"(d[8]), "+f"(d[9]), "+f"(d[10]), "+f"(d[11]), "+f"(d[12]), "+f"(d[13]), "+f"(d[14]), "+f"(d[15]),
        "+f"(d[16]), "+f"(d[17]), "+f"(d[18]), "+f"(d[19]), "+f"(d[20]), "+f"(d[21]), "+f"(d[22]), "+f"(d[23]),
        "+f"(d[24]), "+f"(d[25]), "+f"(d[26]), "+f"(d[27]), "+f"(d[28]), "+f"(d[29]), "+f"(d[30]), "+f"(d[31]),
        "+f"(d[32]), "+f"(d[33]), "+f"(d[34]), "+f"(d[35]), "+f"(d[36]), "+f"(d[37]), "+f"(d[38]), "+f"(d[39]),
        "+f"(d[40]), "+f"(d[41]), "+f"(d[42]), "+f"(d[43]), "+f"(d[44]), "+f"(d[45]), "+f"(d[46]), "+f"(d[47])
      : "l"(da), "l"(db), "r"(acc));
}
__device__ __forceinline__ void mma_ss_n64_bf16_f32(float (&d)[32], uint64_t da, uint64_t db, int acc) {
  asm volatile(
      "{\n.reg .pred p;\nsetp.ne.b32 p, %34, 0;\n"
      "wgmma.mma_async.sync.aligned.m64n64k16.f32.bf16.bf16 {"
      "%0, %1, %2, %3, %4, %5, %6, %7, %8, %9, %10, %11, %12, %13, %14, %15, %16, %17, %18, %19, %20, %21, %22, "
      "%23, %24, %25, %26, %27, %28, %29, %30, %31"
      "}, %32, %33, p, 1, 1, 0, 1;\n}\n"
      : "+f"(d[0]), "+f"(d[1]), "+f"(d[2]), "+f"(d[3]), "+f"(d[4]), "+f"(d[5]), "+f"(d[6]), "+f"(d[7]),
        "+f"(d[8]), "+f"(d[9]), "+f"(d[10]), "+f"(d[11]), "+f"(d[12]), "+f"(d[13]), "+f"(d[14]), "+f"(d[15]),
        "+f"(d[16]), "+f"(d[17]), "+f"(d[18]), "+f"(d[19]), "+f"(d[20]), "+f"(d[21]), "+f"(d[22]), "+f"(d[23]),
        "+f"(d[24]), "+f"(d[25]), "+f"(d[26]), "+f"(d[27]), "+f"(d[28]), "+f"(d[29]), "+f"(d[30]), "+f"(d[31])
      : "l"(da), "l"(db), "r"(acc));
}
__device__ __forceinline__ void mma_ss_n128_bf16_f32(float (&d)[64], uint64_t da, uint64_t db, int acc) {
  asm volatile(
      "{\n.reg .pred p;\nsetp.ne.b32 p, %66, 0;\n"
      "wgmma.mma_async.sync.aligned.m64n128k16.f32.bf16.bf16 {"
      "%0, %1, %2, %3, %4, %5, %6, %7, %8, %9, %10, %11, %12, %13, %14, %15, %16, %17, %18, %19, %20, %21, %22, "
      "%23, %24, %25, %26, %27, %28, %29, %30, %31, %32, %33, %34, %35, %36, %37, %38, %39, %40, %41, %42, %43, "
      "%44, %45, %46, %47, %48, %49, %50, %51, %52, %53, %54, %55, %56, %57, %58, %59, %60, %61, %62, %63"
      "}, %64, %65, p, 1, 1, 0, 1;\n}\n"
      : "+f"(d[0]), "+f"(d[1]), "+f"(d[2]), "+f"(d[3]), "+f"(d[4]), "+f"(d[5]), "+f"(d[6]), "+f"(d[7]),
        "+f"(d[8]), "+f"(d[9]), "+f"(d[10]), "+f"(d[11]), "+f"(d[12]), "+f"(d[13]), "+f"(d[14]), "+f"(d[15]),
        "+f"(d[16]), "+f"(d[17]), "+f"(d[18]), "+f"(d[19]), "+f"(d[20]), "+f"(d[21]), "+f"(d[22]), "+f"(d[23]),
        "+f"(d[24]), "+f"(d[25]), "+f"(d[26]), "+f"(d[27]), "+f"(d[28]), "+f"(d[29]), "+f"(d[30]), "+f"(d[31]),
        "+f"(d[32]), "+f"(d[33]), "+f"(d[34]), "+f"(d[35]), "+f"(d[36]), "+f"(d[37]), "+f"(d[38]), "+f"(d[39]),
        "+f"(d[40]), "+f"(d[41]), "+f"(d[42]), "+f"(d[43]), "+f"(d[44]), "+f"(d[45]), "+f"(d[46]), "+f"(d[47]),
        "+f"(d[48]), "+f"(d[49]), "+f"(d[50]), "+f"(d[51]), "+f"(d[52]), "+f"(d[53]), "+f"(d[54]), "+f"(d[55]),
        "+f"(d[56]), "+f"(d[57]), "+f"(d[58]), "+f"(d[59]), "+f"(d[60]), "+f"(d[61]), "+f"(d[62]), "+f"(d[63])
      : "l"(da), "l"(db), "r"(acc));
}
template <int ACC>
__device__ __forceinline__ void mma_rs_n128_f16_f16(uint32_t (&d)[32], uint32_t a0, uint32_t a1, uint32_t a2, uint32_t a3, uint64_t db) {
  asm volatile(
      "{\n.reg .pred p;\nsetp.ne.b32 p, %37, 0;\n"
      "wgmma.mma_async.sync.aligned.m64n128k16.f16.f16.f16 {"
      "%0, %1, %2, %3, %4, %5, %6, %7, %8, %9, %10, %11, %12, %13, %14, %15, %16, %17, %18, %19, %20, %21, %22, "
      "%23, %24, %25, %26, %27, %28, %29, %30, %31"
      "}, {%32, %33, %34, %35}, %36, p, 1, 1, 0;\n}\n"
      : "+r"(d[0]), "+r"(d[1]), "+r"(d[2]), "+r"(d[3]), "+r"(d[4]), "+r"(d[5]), "+r"(d[6]), "+r"(d[7]),
        "+r"(d[8]), "+r"(d[9]), "+r"(d[10]), "+r"(d[11]), "+r"(d[12]), "+r"(d[13]), "+r"(d[14]), "+r"(d[15]),
        "+r"(d[16]), "+r"(d[17]), "+r"(d[18]), "+r"(d[19]), "+r"(d[20]), "+r"(d[21]), "+r"(d[22]), "+r"(d[23]),
        "+r"(d[24]), "+r"(d[25]), "+r"(d[26]), "+r"(d[27]), "+r"(d[28]), "+r"(d[29]), "+r"(d[30]), "+r"(d[31])
      : "r"(a0), "r"(a1), "r"(a2), "r"(a3), "l"(db), "n"(ACC));
}
template <int ACC>
__device__ __forceinline__ void mma_rs_n32_f16_f16(uint32_t (&d)[8], uint32_t a0, uint32_t a1, uint32_t a2, uint32_t a3, uint64_t db) {
  asm volatile(
      "{\n.reg .pred p;\nsetp.ne.b32 p, %13, 0;\n"
      "wgmma.mma_async.sync.aligned.m64n32k16.f16.f16.f16 {"
      "%0, %1, %2, %3, %4, %5, %6, %7"
      "}, {%8, %9, %10, %11}, %12, p, 1, 1, 1;\n}\n"
      : "+r"(d[0]), "+r"(d[1]), "+r"(d[2]), "+r"(d[3]), "+r"(d[4]), "+r"(d[5]), "+r"(d[6]), "+r"(d[7])
      : "r"(a0), "r"(a1), "r"(a2), "r"(a3), "l"(db), "n"(ACC));
}
__device__ __forceinline__ void mma_ss_n64w_bf16_f32(float (&d)[64], uint64_t da, uint64_t db, int acc) {
  asm volatile(
      "{\n.reg .pred p;\nsetp.ne.b32 p, %34, 0;\n"
      "wgmma.mma_async.sync.aligned.m64n64k16.f32.bf16.bf16 {"
      "%0, %1, %2, %3, %4, %5, %6, %7, %8, %9, %10, %11, %12, %13, %14, %15, %16, %17, %18, %19, %20, %21, %22, "
      "%23, %24, %25, %26, %27, %28, %29, %30, %31"
      "}, %32, %33, p, 1, 1, 0, 1;\n}\n"
      : "+f"(d[0]), "+f"(d[1]), "+f"(d[2]), "+f"(d[3]), "+f"(d[4]), "+f"(d[5]), "+f"(d[6]), "+f"(d[7]),
        "+f"(d[8]), "+f"(d[9]), "+f"(d[10]), "+f"(d[11]), "+f"(d[12]), "+f"(d[13]), "+f"(d[14]), "+f"(d[15]),
        "+f"(d[16]), "+f"(d[17]), "+f"(d[18]), "+f"(d[19]), "+f"(d[20]), "+f"(d[21]), "+f"(d[22]), "+f"(d[23]),
        "+f"(d[24]), "+f"(d[25]), "+f"(d[26]), "+f"(d[27]), "+f"(d[28]), "+f"(d[29]), "+f"(d[30]), "+f"(d[31])
      : "l"(da), "l"(db), "r"(acc));
}

__device__ __forceinline__ uint32_t exp2_mufu(uint32_t x) {
  uint32_t r;
  asm("ex2.approx.f16x2 %0, %1;" : "=r"(r) : "r"(x));
  return r;
}
__device__ __forceinline__ uint32_t exp2_poly(uint32_t x) {
  uint32_t t, nn, f, q, e;
  asm("add.rn.f16x2 %0, %1, %2;" : "=r"(t) : "r"(x), "r"(0x66206620u));
  asm("sub.rn.f16x2 %0, %1, %2;" : "=r"(nn) : "r"(0x66206620u), "r"(t));
  asm("add.rn.f16x2 %0, %1, %2;" : "=r"(f) : "r"(x), "r"(nn));
  asm("fma.rn.f16x2 %0, %1, %2, %3;" : "=r"(q) : "r"(f), "r"(0xB3A4B3A4u), "r"(0xB9A0B9A0u));
  asm("fma.rn.f16x2 %0, %1, %2, %3;" : "=r"(q) : "r"(q), "r"(f), "r"(0xBC00BC00u));
  asm("mad.lo.u32 %0, %1, 1024, %2;" : "=r"(e) : "r"(t), "r"(0u - (0x198u << 16)));
  return __viaddmin_u16x2(q, e, 0x7C007C00u);
}

#define ATT_CH 4
#define ATT_SYNC 0
#define ATT_EVERY 1
#define ATT_WAIT 5
template <int FIRST>
__device__ __forceinline__ void attn_tile(uint32_t (&s)[32], uint32_t (&oh)[8], const uint32_t (&q)[8], uint64_t kd, uint64_t vd, uint32_t sb,
                                          int kbar, int ring) {
  uint32_t p[32];
  if (ATT_SYNC > 0 && (ATT_EVERY || FIRST)) bar_sync(11 + ring, 256);
  if (ATT_WAIT == 2) mbar_wait(sb, kbar);
  uint32_t have = 0;
  if (ATT_WAIT >= 5) have = mbar_test(sb, kbar);
#pragma unroll
  for (int c = 0; c < 8; c += ATT_CH) {
#pragma unroll
    for (int g = 4 * c; g < 4 * (c + ATT_CH); g++) p[g] = ((POLY_MASK >> g) & 1) ? exp2_poly(s[g]) : exp2_mufu(s[g]);
#pragma unroll
    for (int g = 4 * c; g < 4 * (c + ATT_CH); g++) asm volatile("" : "+r"(p[g])::"memory");
    if (ATT_SYNC > 0 && (ATT_EVERY || FIRST) && c + ATT_CH == ATT_SYNC) asm volatile("bar.arrive %0, 256;" ::"r"(11 + ((ring + 1) & 3)) : "memory");
    if (ATT_WAIT == 3 && c + ATT_CH == 8) mbar_wait(sb, kbar);
    if (ATT_WAIT == 5 && c + ATT_CH == 8 && !have) mbar_wait(sb, kbar);
    wg_fence();
#pragma unroll
    for (int k = c; k < c + ATT_CH; k++) {
      if (FIRST && k == 0) mma_rs_n32_f16_f16<0>(oh, p[0], p[1], p[2], p[3], vd);
      else mma_rs_n32_f16_f16<1>(oh, p[4 * k], p[4 * k + 1], p[4 * k + 2], p[4 * k + 3], dadd(vd, 1024 * k));
    }
  }
  if (ATT_WAIT == 4 && !FIRST) {
    mbar_wait(sb, kbar);
    mbar_wait(sb, kbar == B_KVFULL + 15 ? kbar : kbar + 1);
    wg_fence();
  }
  if (ATT_WAIT == 6) {
    if (!have) mbar_wait(sb, kbar);
    wg_fence();
  }
  if (ATT_WAIT == 0) {
    mbar_wait(sb, kbar);
    wg_fence();
  }
  mma_rs_n128_f16_f16<0>(s, q[0], q[1], q[2], q[3], kd);
  mma_rs_n128_f16_f16<1>(s, q[4], q[5], q[6], q[7], dadd(kd, 32));
  wg_commit();
  wg_wait<0>();
  pin(p); pin(s); pin(oh);
}

__device__ __noinline__ void project_row(const __nv_bfloat16* __restrict__ xr, const __nv_bfloat16* __restrict__ w, float* dst) {
  float s = 0.f, v = 0.f;
#pragma unroll 1
  for (int k = 0; k < ND; k++) s += __bfloat162float(xr[k]);
  const float mu = s * (1.f / ND);
#pragma unroll 1
  for (int k = 0; k < ND; k++) { const float d = __bfloat162float(xr[k]) - mu; v += d * d; }
  const float rs = 1.f / sqrtf(v * (1.f / ND) + 1e-5f);
#pragma unroll 1
  for (int d0 = 0; d0 < 28; d0 += 4) {
    float a0 = 0.f, a1 = 0.f, a2 = 0.f, a3 = 0.f;
#pragma unroll 1
    for (int k = 0; k < ND; k++) {
      const float a = (__bfloat162float(xr[k]) - mu) * rs;
      const uint2 ww = *reinterpret_cast<const uint2*>(w + (size_t)k * (3 * ND) + d0);
      a0 = fmaf(a, b_lo(ww.x), a0); a1 = fmaf(a, b_hi(ww.x), a1); a2 = fmaf(a, b_lo(ww.y), a2); a3 = fmaf(a, b_hi(ww.y), a3);
    }
    dst[d0] = a0; dst[d0 + 1] = a1; dst[d0 + 2] = a2; dst[d0 + 3] = a3;
  }
}
__device__ __noinline__ void attention_exact(const __nv_bfloat16* __restrict__ x, const __nv_bfloat16* __restrict__ wqkv, int h, int row0,
                                             uint32_t stage) {
  const int lane = threadIdx.x & 31;
  float qv[28], kv[28], vv[28], o[28], m = -INFINITY, l = 0.f;
  project_row(x + (size_t)(row0 + (lane & 15)) * ND, wqkv + 28 * h, qv);
#pragma unroll 1
  for (int d = 0; d < 28; d++) o[d] = 0.f;
#pragma unroll 1
  for (int k0 = 0; k0 < NS; k0 += 32) {
    project_row(x + (size_t)(k0 + lane) * ND, wqkv + ND + 28 * h, kv);
    project_row(x + (size_t)(k0 + lane) * ND, wqkv + 2 * ND + 28 * h, vv);
#pragma unroll 1
    for (int t = 0; t < 32; t++) {
      float s = 0.f;
#pragma unroll 1
      for (int d = 0; d < 28; d++) s = fmaf(qv[d], __shfl_sync(0xffffffffu, kv[d], t), s);
      s *= 0.18898223650461362f;
      const float mn = fmaxf(m, s);
      const float corr = expf(m - mn), p = expf(s - mn);
      m = mn;
      l = l * corr + p;
#pragma unroll 1
      for (int d = 0; d < 28; d++) o[d] = o[d] * corr + p * __shfl_sync(0xffffffffu, vv[d], t);
    }
  }
  if (lane < 16) {
#pragma unroll 1
    for (int d = 0; d < 32; d += 2) {
      const int c = (d + 4 * (h & 1)) & 31;
      sts_u32(stage + lane * 64 + (((c >> 3) ^ ((lane >> 1) & 3)) << 4) + 2 * (c & 7), d < 28 ? pack_b2(o[d] / l, o[d + 1] / l) : 0u);
    }
  }
}

__device__ __forceinline__ uint32_t wslot(int s) {
  const int k = s % 6;
  return k < 2 ? SM_R + (k + 1) * 16384 : k < 5 ? SM_G + (k - 2) * 16384 : SM_R;
}
__device__ __forceinline__ int wrap7(int c) { return c >= 7 ? c - 7 : c; }
__device__ __forceinline__ int f2stage(int rank, int pair, int t) {
  const int n = 4 - rank;
  return t < n ? 14 + 2 * t + pair : 14 + n + pair * (7 - n) + t;
}
__device__ __forceinline__ int stage_pair(int rank, int s) {
  const int n = 4 - rank;
  return s < 14 + 2 * n ? (s & 1) : (s - 21 >= n);
}

template <bool WIDE, bool SECOND, class F>
__device__ __forceinline__ void ffn_loop(float (&acc)[64], uint32_t sb, int first, int rank, int pair, int half, F&& extra PROF_PARAM) {
  int prev = 0;
#pragma unroll 1
  for (int t = 0; t < 7; t++) {
    const int c = wrap7(first + t), s = SECOND ? f2stage(rank, pair, t) : 2 * t + pair;
    const uint64_t da = mkdesc(sb + SM_A + c * 16384 + half * 8192, 16, 1024, 1);
    const uint64_t db = mkdesc(sb + wslot(s), 8192, 1024, 1);
    mbar_wait(sb, (SECOND ? B_GFULL : B_HFULL) + c);
    PSTAGE(2, s);
    mbar_wait(sb, B_WFULL + s);
    PSTAGE(1, s);
    wg_fence();
#pragma unroll
    for (int k = 0; k < 4; k++) {
      if (WIDE) mma_ss_n128_bf16_f32(acc, dadd(da, 32 * k), dadd(db, 2048 * k), (t | k) != 0);
      else mma_ss_n64w_bf16_f32(acc, dadd(da, 32 * k), dadd(db, 2048 * k), (t | k) != 0);
    }
    wg_commit();
    extra(t);
    wg_wait<1>();
    if (t > 0 && fresh_lane() == 0) mbar_arrive(sb + SM_BAR + 8 * (B_WREL + prev));
    prev = s;
  }
}

__device__ __forceinline__ void phase_c(uint32_t sb, int g, int j, const __nv_bfloat16* __restrict__ x, const __nv_bfloat16* __restrict__ w1,
                                        __nv_bfloat16* __restrict__ out PROF_PARAM) {
  const int tid = fresh_tid(), lane = tid & 31, wg = tid >> 7, warp4 = (tid >> 5) & 3, c4 = lane & 3;
  const int rank = j & 1, ii = j >> 1, pair = wg >> 1, half = wg & 1;
  const uint32_t bar = sb + SM_BAR, par = epoch(sb) & 1;
  const int rl = 64 * half + 16 * warp4 + (lane >> 2);
  const int srow = 64 * half + 16 * warp4 + (lane & 7) + 8 * ((lane >> 3) & 1);
  const uint32_t soff = srow * 128 + (((lane >> 4) ^ (srow & 7)) << 4);
  if (pair == 0) {
    uint32_t hp[16];
    float acc[32];
    if (j < 7) {
      const __nv_bfloat16* xp = x + (size_t)(128 * g + rl) * ND + 64 * j + 2 * c4;
#pragma unroll
      for (int n = 0; n < 16; n++) hp[n] = __ldg(reinterpret_cast<const uint32_t*>(xp + (n & 1) * 8 * ND + 8 * (n >> 1)));
      mbar_wait(sb, B_WOFULL);
    }
#pragma unroll 1
    for (int c = 0; c < 8; c++) {
      const uint64_t da = mkdesc(sb + SM_A + c * 16384 + half * 4096, 16, 512, 2);
      const uint64_t db = mkdesc(sb + SM_W + c * 56 * 128, 8192, 1024, 1);
      mbar_wait(sb, B_OFULL + c);
      if (c == 0) PMARK(wg, 7);
      wg_fence();
#pragma unroll
      for (int k = 0; k < 4; k++)
        mma_ss_n64_bf16_f32(acc, dadd(da, 8192 * (k >> 1) + 32 * (k & 1)), dadd(db, 3072 * (k >> 1) + 2048 * (k & 1)), (c | k) != 0);
      wg_commit();
    }
    wg_wait<0>();
    pin(acc);
    PMARK(wg, 8);
    if (lane == 0) {
      mbar_arrive(bar + 8 * B_WODONE);
      mbar_arrive(bar + 8 * B_AFREE2);
      mbar_arrive_remote(mapa(bar + 8 * B_AFREE2, rank ^ 1));
    }
    if (j < 7) {
#pragma unroll
      for (int n = 0; n < 16; n++) hp[n] = pack_b2(acc[2 * n] + b_lo(hp[n]), acc[2 * n + 1] + b_hi(hp[n]));
      bar_sync(6, 256);
#pragma unroll
      for (int n = 0; n < 4; n++) stsm4(sb + SM_A + j * 16384 + (soff ^ (32 * n)), hp[4 * n], hp[4 * n + 1], hp[4 * n + 2], hp[4 * n + 3]);
      fence_async_smem();
      bar_sync(2 + wg, 128);
      if (warp4 == 0 && elect_one()) {
        bulk_s2g(g_h + (size_t)(g * 7 + j) * 16384 + half * 8192, sb + SM_A + j * 16384 + half * 8192, 8192);
        mbar_arrive(bar + 8 * (B_HFULL + j));
        bulk_commit_wait();
        fence_async_all();
        red_add(g_flagH + (g * 8 + j) * 8);
      }
      __syncwarp();
      float s[2] = {0.f, 0.f}, v[2] = {0.f, 0.f};
#pragma unroll
      for (int n = 0; n < 16; n++) s[n & 1] += b_lo(hp[n]) + b_hi(hp[n]);
      s[0] = quad_sum(s[0]) * (1.f / 64);
      s[1] = quad_sum(s[1]) * (1.f / 64);
#pragma unroll
      for (int n = 0; n < 16; n++) {
        const float d0 = b_lo(hp[n]) - s[n & 1], d1 = b_hi(hp[n]) - s[n & 1];
        v[n & 1] = fmaf(d0, d0, fmaf(d1, d1, v[n & 1]));
      }
      v[0] = quad_sum(v[0]);
      v[1] = quad_sum(v[1]);
      if (c4 < 2) st_tag2(g_st2 + j * NS + 128 * g + rl + 8 * c4, c4 ? s[1] : s[0], c4 ? v[1] : v[0], par);
      PMARK(wg, 9);
    }
  } else if (half == 0) {
    const int t = rank && (tid & 127) >= 96 ? 0 : tid & 127;
    const uint32_t* wp = reinterpret_cast<const uint32_t*>(w1 + (size_t)(28 * g) * NF + 448 * ii + 256 * rank) + t;
    float s0 = 0.f, s1 = 0.f;
#pragma unroll 14
    for (int k = 0; k < 28; k++) {
      const uint32_t v = __ldg(wp + k * (NF / 2));
      s0 += b_lo(v);
      s1 += b_hi(v);
    }
    st_tag2(g_cs1 + (j * 16 + g) * 128 + t, s0, s1, par);
    mbar_wait(sb, B_WODONE);
    s0 = s1 = 0.f;
#pragma unroll 1
    for (int k0 = 0; k0 < 16; k0 += 8) {
      const uint2* p = g_cs1 + (j * 16 + k0) * 128 + t;
      uint2 v[8];
      uint32_t bad;
      do {
        bad = 0;
#pragma unroll
        for (int k = 0; k < 8; k++) v[k] = ld_rlx2(p + 128 * k);
#pragma unroll
        for (int k = 0; k < 8; k++) bad |= (v[k].x ^ par) | (v[k].y ^ par);
      } while ((bad & 1u) != 0 && !timed_out(sb));
#pragma unroll
      for (int k = 0; k < 8; k++) { s0 += __uint_as_float(v[k].x); s1 += __uint_as_float(v[k].y); }
    }
    sts_f2(sb + SM_CS1 + 8 * t, s0, s1);
    __syncwarp();
    if (lane == 0) mbar_arrive(bar + 8 * B_CS1);
    PMARK(wg, 9);
  }
  {
    float acc[64];
    const bool wide = pair || !rank;
    const uint2* sp = g_st2 + c4 * NS + 128 * g + rl;
    const int c2 = c4 < 3 ? 4 * NS : 0;
    uint2 u[4];
    auto stats = [&](int t) {
      if (t == 4) { u[0] = ld_rlx2(sp); u[1] = ld_rlx2(sp + 8); u[2] = ld_rlx2(sp + c2); u[3] = ld_rlx2(sp + c2 + 8); }
    };
    if (wide) ffn_loop<true, false>(acc, sb, j == 7 ? 6 : j, rank, pair, half, stats PROF_ARG);
    else ffn_loop<false, false>(acc, sb, j == 7 ? 6 : j, rank, pair, half, stats PROF_ARG);
    while ((((u[0].x ^ par) | (u[0].y ^ par) | (u[1].x ^ par) | (u[1].y ^ par) | (u[2].x ^ par) | (u[2].y ^ par) | (u[3].x ^ par) | (u[3].y ^ par)) & 1u) != 0 &&
           !timed_out(sb))
      stats(4);
    float mu[2], hr[2];
#pragma unroll
    for (int e = 0; e < 2; e++) {
      const float w2 = c4 < 3 ? 1.f : 0.f, ma = __uint_as_float(u[e].x), mb = __uint_as_float(u[2 + e].x);
      mu[e] = quad_sum(fmaf(w2, mb, ma)) * (1.f / 7);
      const float da = ma - mu[e], db = mb - mu[e];
      const float v = quad_sum(fmaf(64.f * da, da, __uint_as_float(u[e].y)) + w2 * fmaf(64.f * db, db, __uint_as_float(u[2 + e].y)));
      hr[e] = 0.5f * rsqrtf(v * (1.f / ND) + 1e-5f);
    }
    mbar_wait(sb, B_CS1);
    PMARK(wg, 21);
    wg_wait<0>();
    pin(acc);
    PMARK(wg, 12);
    if (lane == 0) {
      mbar_arrive(bar + 8 * (B_WREL + 12 + pair));
      mbar_arrive(bar + 8 * B_AFREE3_L);
      mbar_arrive_remote(mapa(bar + 8 * B_AFREE3_R, rank ^ 1));
    }
    const int kap0 = rank ? 4 + pair : 2 * pair;
    float cur[32];
#pragma unroll
    for (int n = 0; n < 32; n++) asm volatile("mov.b32 %0, %1;" : "=f"(cur[n]) : "f"(acc[n]));
#pragma unroll 1
    for (int a = 0; a <= (int)wide; a++) {
      uint32_t gp[16];
      const uint32_t csb = sb + SM_CS1 + (kap0 - 4 * rank + a) * 256 + 8 * c4;
#pragma unroll
      for (int n = 0; n < 8; n++) {
        const float2 cs = lds_f2(csb + 32 * n);
        float z[4] = {fmaf(-mu[0], cs.x, cur[4 * n]) * hr[0], fmaf(-mu[0], cs.y, cur[4 * n + 1]) * hr[0],
                      fmaf(-mu[1], cs.x, cur[4 * n + 2]) * hr[1], fmaf(-mu[1], cs.y, cur[4 * n + 3]) * hr[1]};
#pragma unroll
        for (int e = 0; e < 4; e++) {
          float th;
          asm("tanh.approx.f32 %0, %1;" : "=f"(th) : "f"(z[e]));
          z[e] = fmaf(z[e], th, z[e]);
        }
        gp[2 * n] = pack_b2(z[0], z[1]);
        gp[2 * n + 1] = pack_b2(z[2], z[3]);
      }
      mbar_wait(sb, B_AFREE3_L);
#pragma unroll
      for (int n = 0; n < 4; n++) stsm4(sb + SM_A + (kap0 + a) * 16384 + (soff ^ (32 * n)), gp[4 * n], gp[4 * n + 1], gp[4 * n + 2], gp[4 * n + 3]);
      fence_async_smem();
      __syncwarp();
      if (lane == 0) mbar_arrive(bar + 8 * (B_GFULL + kap0 + a));
#pragma unroll
      for (int n = 0; n < 32; n++) asm volatile("mov.b32 %0, %1;" : "=f"(cur[n]) : "f"(acc[32 + n]));
    }
    PMARK(wg, 13);
  }
  const bool wide = !pair || rank;
  const int oc = rank ? 3 + 2 * pair : 2 * pair, orow = rl + 8 * (ii >> 1);
  uint32_t res[8];
  {
    const unsigned char* hp = g_h + (size_t)(g * 7 + oc) * 16384 + orow * 128 + 4 * c4;
#pragma unroll
    for (int n = 0; n < 8; n++)
      asm volatile("ld.relaxed.gpu.global.u32 %0, [%1];" : "=r"(res[n])
                   : "l"(hp + (n >> 2) * (wide ? 16384 : 0) + (((4 * (ii & 1) + (n & 3)) ^ (orow & 7)) << 4)) : "memory");
  }
  float acc[64];
  auto nothing = [](int) {};
  if (wide) ffn_loop<true, true>(acc, sb, 4 * rank, rank, pair, half, nothing PROF_ARG);
  else ffn_loop<false, true>(acc, sb, 4 * rank, rank, pair, half, nothing PROF_ARG);
  wg_wait<0>();
  pin(acc);
  PMARK(wg, 14);
  asm volatile("barrier.cluster.arrive.relaxed.aligned;" ::: "memory");
  float own[16];
  uint4* pbase = g_part + (size_t)((g * 2 + rank) * 16) * 1024 + wg * 256 + (tid & 127);
#pragma unroll
  for (int a = 0; a < 2; a++) {
#pragma unroll
    for (int o = 0; o < 4; o++) {
      const int i0 = 32 * a + 16 * (o & 1) + 2 * (o >> 1);
      if (o == ii) {
#pragma unroll
        for (int k = 0; k < 4; k++) { own[8 * a + 2 * k] = acc[i0 + 4 * k]; own[8 * a + 2 * k + 1] = acc[i0 + 4 * k + 1]; }
      } else if (a == 0 || wide) {
        st_rec(pbase + (o * 4 + ii) * 1024 + a * 128, pack_b2(acc[i0], acc[i0 + 1]) | 1u, pack_b2(acc[i0 + 4], acc[i0 + 5]),
               pack_b2(acc[i0 + 8], acc[i0 + 9]), pack_b2(acc[i0 + 12], acc[i0 + 13]));
      }
    }
  }
  PMARK(wg, 24);
  uint4 in[6];
  const uint4* src = pbase + ii * 4096;
  do {
#pragma unroll
    for (int u = 0; u < 6; u++) in[u] = ld_rec(src + ((ii + 1 + (u >> 1)) & 3) * 1024 + (u & 1) * (wide ? 128 : 0));
  } while ((in[0].x & in[1].x & in[2].x & in[3].x & in[4].x & in[5].x & 1u) == 0 && !timed_out(sb));
  PMARK(wg, 25);
  __nv_bfloat16* op = out + (size_t)(128 * g + orow) * ND + 64 * oc + 32 * (ii & 1) + 2 * c4;
#pragma unroll
  for (int a = 0; a < 2; a++) {
    if (a == 0 || wide) {
#pragma unroll
      for (int k = 0; k < 4; k++) {
        float lo = own[8 * a + 2 * k] + b_lo(res[4 * a + k]), hi = own[8 * a + 2 * k + 1] + b_hi(res[4 * a + k]);
#pragma unroll
        for (int u = 0; u < 3; u++) {
          const uint4 v = in[2 * u + a];
          const uint32_t w = k == 0 ? v.x : k == 1 ? v.y : k == 2 ? v.z : v.w;
          lo += b_lo(w);
          hi += b_hi(w);
        }
        *reinterpret_cast<uint32_t*>(op + 64 * a + 8 * k) = pack_b2(lo, hi);
      }
    }
  }
  PMARK(wg, 15);
  PDUMP(wg);
}

__global__ void __cluster_dims__(2, 1, 1) __launch_bounds__(NTHREADS, 1)
fused_block_kernel(const __grid_constant__ CUtensorMap tmX, const __grid_constant__ CUtensorMap tmWq, const __grid_constant__ CUtensorMap tmWo,
                   const __grid_constant__ CUtensorMap tmW1, const __grid_constant__ CUtensorMap tmW2,
                   const __nv_bfloat16* __restrict__ x, const __nv_bfloat16* __restrict__ wqkv, const __nv_bfloat16* __restrict__ wo,
                   const __nv_bfloat16* __restrict__ w1, const __nv_bfloat16* __restrict__ w2, __nv_bfloat16* __restrict__ out) {
  extern __shared__ __align__(1024) unsigned char smem[];
  const uint32_t sb = (uint32_t)__cvta_generic_to_shared(smem);
  const uint32_t bar = sb + SM_BAR;
  const int tid = threadIdx.x, warp = tid >> 5;
  const int b = blockIdx.x, rank = b & 1;
  const int h = b & 15, r = b >> 4, g = b >> 3, j = b & 7;
  const int odd = h & 1, wcol0 = 28 * h - 4 * odd;
  const uint32_t st_stage = SM_W + (r == 6 ? 4 : 6) * 12288;
  if (warp == 16) {
    if (elect_one()) {
      asm volatile("prefetch.tensormap [%0];" ::"l"(&tmWq) : "memory");
      asm volatile("prefetch.tensormap [%0];" ::"l"(&tmX) : "memory");
#pragma unroll
      for (int i = 0; i < B_KVFULL; i++) mbar_init(bar + 8 * i, bar_count(i, 0, 0));
      uint32_t t;
      asm volatile("mov.u32 %0, %%clock;" : "=r"(t));
      sts_u32(sb + SM_EP + 16, t);
      asm volatile("fence.mbarrier_init.release.cluster;" ::: "memory");
      fence_async_smem();
    }
    __syncwarp();
    asm volatile("barrier.cluster.arrive.relaxed.aligned;" ::: "memory");
    if (elect_one()) {
      mbar_expect(bar + 8 * B_WQ, 12288);
      tma3d(sb + SM_W, &tmWq, wcol0, 0, 0, bar + 8 * B_WQ);
#pragma unroll
      for (int c = 0; c < 13; c++) mbar_expect(bar + 8 * (c < 7 ? B_XFULL + c : B_WQ + c - 6), c < 7 ? 32768 : 12288);
    }
    __syncwarp();
    asm volatile("bar.arrive 1, 640;" ::: "memory");
    PMARK(4, 2);
    asm volatile("barrier.cluster.wait.acquire.aligned;" ::: "memory");
    if (elect_one()) {
      const int wr = r < 7 ? r : 1;
#pragma unroll 1
      for (int c = 0; c < 7; c++) {
        if (c >= 4) mbar_wait(sb, B_XREL + c - 4);
        tma2d_mc(sb + (c & 3) * 32768 + rank * 16384, &tmX, 64 * c, 256 * r + 128 * rank, bar + 8 * (B_XFULL + c));
        if (c == 3) mbar_wait(sb, B_STDONE);
        if (c == 0) {
          mbar_expect(bar + 8 * B_ST, 16 + 16 * 896);
          bulk_g2s(sb + SM_EP, g_epoch + b, 16, bar + 8 * B_ST);
          bulk_g2s(sb + st_stage, x + (size_t)(256 * r + 16 * h) * ND, 16 * 896, bar + 8 * B_ST);
        }
        if (c == 0 && wr > 1) tma3d(sb + SM_W + wr * 12288, &tmWq, wcol0, 64 * wr, 0, bar + 8 * (B_WQ + wr));
        if (c < 6 && (c + 1 != wr || wr == 1)) tma3d(sb + SM_W + (c + 1) * 12288, &tmWq, wcol0, 64 * (c + 1), 0, bar + 8 * (B_WQ + c + 1));
      }
    }
    __syncwarp();
    PMARK(4, 0);
  } else {
    asm volatile("barrier.cluster.arrive.relaxed.aligned;" ::: "memory");
    bar_sync(1, 640);
    if (warp == 18) {
      const int lane = tid & 31;
      bar_sync(8, 544);
      const uint32_t par = epoch(sb) & 1;
      if (lane < 24) {
        float s[4] = {0.f, 0.f, 0.f, 0.f};
#pragma unroll 1
        for (int k = 0; k < (r < 7 ? 8 : 0); k++) {
          const float2 t0 = lds_f2(sb + SM_RED + (k * 24 + lane) * 16), t1 = lds_f2(sb + SM_RED + (k * 24 + lane) * 16 + 8);
          s[0] += t0.x; s[1] += t0.y; s[2] += t1.x; s[3] += t1.y;
        }
        st_rec(g_cs0 + (h * 8 + r) * 24 + lane, tagw(s[0], par), __float_as_uint(s[1]), __float_as_uint(s[2]), __float_as_uint(s[3]));
      }
      const uint4* p = g_cs0 + (h * 8 + (lane & 7)) * 24 + (lane >> 3);
      uint4 v[6];
      do {
#pragma unroll
        for (int k = 0; k < 6; k++) v[k] = ld_rec(p + 4 * k);
      } while (__any_sync(0xffffffffu, (((v[0].x ^ par) | (v[1].x ^ par) | (v[2].x ^ par) | (v[3].x ^ par) | (v[4].x ^ par) | (v[5].x ^ par)) & 1u) != 0) &&
               !timed_out(sb));
#pragma unroll
      for (int k = 0; k < 6; k++) {
        float s[4] = {__uint_as_float(v[k].x), __uint_as_float(v[k].y), __uint_as_float(v[k].z), __uint_as_float(v[k].w)};
#pragma unroll
        for (int o = 1; o < 8; o <<= 1)
#pragma unroll
          for (int e = 0; e < 4; e++) s[e] += __shfl_xor_sync(0xffffffffu, s[e], o);
        if ((lane & 7) == 0) {
          sts_f2(sb + SM_CS0 + 16 * ((lane >> 3) + 4 * k), s[0], s[1]);
          sts_f2(sb + SM_CS0 + 16 * ((lane >> 3) + 4 * k) + 8, s[2], s[3]);
        }
      }
      __syncwarp();
      if (lane == 0) mbar_arrive(bar + 8 * B_CS0);
      PMARK(6, 0);
    }
  }

  if (warp >= 16) {
    asm volatile("setmaxnreg.dec.sync.aligned.u32 32;");
    if (warp == 16) {
      const int w1c0 = 448 * (j >> 1) + 256 * rank;
      if (elect_one()) {
        mbar_wait(sb, B_KVREL + 1);
        l2_prefetch((const char*)wo + b * 3136, 3136);
        l2_prefetch((const char*)w1 + b * 12544, 12544);
        l2_prefetch((const char*)w2 + b * 12544, 12544);
        mbar_wait(sb, B_KVREL + 4);
        if (j < 7) {
          mbar_expect(bar + 8 * B_WOFULL, 7 * 8192);
#pragma unroll 1
          for (int c = 0; c < 7; c++) tma2d(sb + SM_W + c * 8192, &tmWo, 64 * j, 64 * c, bar + 8 * B_WOFULL);
        }
        uint32_t slot = SM_R + 16384, fb = bar + 8 * B_WFULL;
        auto stage = [&](const CUtensorMap* tm, int col, int row, bool two) {
          if (fb >= bar + 8 * (B_WFULL + 6)) mbar_wait_addr(sb, fb + 8 * (B_WREL - B_WFULL - 6));
          tma2d(sb + slot, tm, col, row, fb);
          if (two) tma2d(sb + slot + 8192, tm, col + 64, row, fb);
          PSTAGE(0, (fb - bar) / 8 - B_WFULL);
          slot = slot == SM_R + 32768 ? SM_G : slot == SM_G + 32768 ? SM_R : slot + 16384;
          fb += 8;
        };
        int c = j == 7 ? 6 : j;
#pragma unroll 1
        for (int t = 0; t < 7; t++) {
          if (t == 1) mbar_wait(sb, B_WODONE);
          stage(&tmW1, w1c0, 64 * c, !rank);
          stage(&tmW1, w1c0 + (rank ? 64 : 128), 64 * c, true);
          c = wrap7(c + 1);
        }
        const int row2 = 448 * (j >> 1), col2 = rank ? 192 : 0;
#pragma unroll 1
        for (int t = 0; t < 4 - rank; t++) {
          stage(&tmW2, col2, row2 + 64 * (4 * rank + t), true);
          stage(&tmW2, col2 + 128, row2 + 64 * (4 * rank + t), rank);
        }
#pragma unroll 1
        for (int t = 0; t < 6 + 2 * rank; t++) {
          const int pair = t >= 3 + rank;
          stage(&tmW2, col2 + 128 * pair, row2 + 64 * (4 - 4 * rank + t - pair * (3 + rank)), !pair || rank);
        }
        PMARK(4, 7);
      }
      __syncwarp();
      if (elect_one()) g_epoch[b].x = epoch(sb);
      PDUMP(4);
    } else if (warp == 17) {
      const int lane = fresh_lane();
      bar_sync(7, 96);
      asm volatile("barrier.cluster.wait.acquire.aligned;" ::: "memory");
      mbar_wait(sb, B_ST);
      const uint32_t ep = 2 * epoch(sb);
#pragma unroll 1
      for (int i = B_KVFULL + 2 + lane; i < B_AFREE3_L; i += 32) {
        uint32_t bytes = 0;
        if (i < B_KVREL) bytes = 16384 + 16 * ((i - B_KVFULL) & 1);
        else if ((i >= B_OFULL && i < B_WOFULL) || (i >= B_HFULL && i < B_WFULL && i != B_HFULL + j) || (i >= B_GFULL && (i - B_GFULL >= 4) != (rank == 1))) bytes = 16384;
        else if (i >= B_WFULL && i < B_WREL) {
          const int pair = stage_pair(rank, i - B_WFULL);
          bytes = (i - B_WFULL < 14 ? (pair || !rank) : (!pair || rank)) ? 16384 : 8192;
        }
        if (bytes) mbar_expect(bar + 8 * i, bytes);
      }
#pragma unroll 1
      for (int rd = -2; rd < 7; rd++) {
        const uint32_t* flag = rd < 5 ? g_flagKV + (h * 8 + ((r + lane) & 7)) * 8 : (rd == 5 ? g_flagO : g_flagH) + (g * 8 + (lane & 7)) * 8;
        uint32_t todo = rd < 0 ? 2u : rd == 0 ? 12u : rd < 5 ? 8u << rd : 0x55u << rank;
        if (rd == 6) todo = ((todo & ~(1u << j)) | (1u << (j ^ 1))) & 0x7Fu;
        mbar_wait(sb, rd > 5 ? B_AFREE2 : rd == 5 ? B_AFREE1 : rd > 0 ? B_KVREL + rd : rd ? B_KVFULL + 1 : B_KVFULL + 3);
        if (rd == 5) PMARK(5, 3);
        if (rd == 6) PMARK(5, 5);
        do {
          uint32_t rdy = todo & __ballot_sync(0xffffffffu, (int)(ld_acquire(flag) - (rd == 5 ? 2 * ep : rd == -2 ? ep - 1 : ep)) >= 0);
          todo &= ~rdy;
          fence_async_all();
          for (; rdy; rdy &= rdy - 1) {
            const int k = __ffs(rdy) - 1;
            if (elect_one()) {
              if (rd < 5) {
                const unsigned char* src = g_kv + (size_t)(h * 8 + ((r + k) & 7)) * 32896;
                const uint32_t dst = sb + ((k + 2) % 3) * 32768, fb = bar + 8 * (B_KVFULL + 2 * k);
                if (rd != -1) bulk_g2s(dst, src, 16384, fb);
                if (rd != -2) {
                  bulk_g2s(dst + 16384, src + 16384, 16384, fb + 8);
                  bulk_g2s(sb + SM_TR + 16 * k, src + 32768, 16, fb + 8);
                }
              } else {
                const unsigned char* src = rd == 5 ? g_O + (size_t)(g * 8 + k) * 16384 : g_h + (size_t)(g * 7 + k) * 16384;
                const uint32_t fb = bar + 8 * ((rd == 5 ? B_OFULL : B_HFULL) + k);
                if (rd == 6 && k == (j ^ 1)) bulk_g2s(sb + SM_A + k * 16384, src, 16384, fb);
                else bulk_g2s_mc(sb + SM_A + k * 16384, src, 16384, fb);
              }
            }
            __syncwarp();
          }
        } while (todo && !timed_out(sb));
        if (rd == -2) PMARK(5, 2);
        if (rd == 5) PMARK(5, 4);
      }
      PMARK(5, 6);
      if (elect_one()) {
        mbar_wait(sb, B_AFREE3_R);
#pragma unroll 1
        for (int k = 4 * rank; k < 4 + 3 * rank; k++) {
          mbar_wait(sb, B_GFULL + k);
          const uint32_t src = sb + SM_A + k * 16384;
          bulk_s2peer(mapa(src, rank ^ 1), src, 16384, mapa(bar + 8 * (B_GFULL + k), rank ^ 1));
        }
      }
      __syncwarp();
      PMARK(5, 7);
      PDUMP(5);
    } else if (warp == 19) {
      const int lane = fresh_lane();
      asm volatile("barrier.cluster.wait.acquire.aligned;" ::: "memory");
      bar_sync(7, 96);
      if (elect_one()) {
        unsigned char* dst = g_kv + (size_t)(h * 8 + r) * 32896;
        uint32_t* flag = g_flagKV + (h * 8 + r) * 8;
        mbar_wait(sb, B_KVFULL);
        const uint32_t ep = 2 * epoch(sb);
        bulk_s2g(dst, sb + SM_KV0, 16384);
        asm volatile("cp.async.bulk.commit_group;" ::: "memory");
        mbar_wait(sb, B_KVFULL + 1);
        bulk_s2g(dst + 16384, sb + SM_KV0 + 16384, 16384);
        bulk_s2g(dst + 32768, sb + SM_TR, 16);
        asm volatile("cp.async.bulk.commit_group;\ncp.async.bulk.wait_group 1;" ::: "memory");
        fence_async_all();
        asm volatile("st.relaxed.gpu.global.u32 [%0], %1;" ::"l"(flag), "r"(ep - 1) : "memory");
        PMARK(5, 0);
        asm volatile("cp.async.bulk.wait_group 0;" ::: "memory");
        fence_async_all();
        asm volatile("st.relaxed.gpu.global.u32 [%0], %1;" ::"l"(flag), "r"(ep) : "memory");
        PMARK(5, 1);
      }
      __syncwarp();
#pragma unroll
      for (int k = 0; k < 4; k++) asm volatile("st.shared.v4.u32 [%0], {%1, %1, %1, %1};" ::"r"(sb + SM_ZERO + 512 * k + 16 * lane), "r"(0) : "memory");
      fence_async_smem();
      __syncwarp();
      if (elect_one()) {
        mbar_wait(sb, B_KVREL + 3);
        uint4* inbox = g_part + (size_t)((g * 2 + rank) * 16 + (j >> 1) * 4) * 1024;
#pragma unroll 1
        for (int k = 0; k < 32; k++)
          if ((k >> 3) != (j >> 1)) bulk_s2g(inbox + 128 * k, sb + SM_ZERO, 2048);
        bulk_commit_wait();
        fence_async_all();
        mbar_arrive(bar + 8 * B_AFREE1);
        mbar_arrive_remote(mapa(bar + 8 * B_AFREE1, rank ^ 1));
      }
      return;
    } else {
      PDUMP(6);
      return;
    }
    asm volatile("barrier.cluster.arrive.relaxed.aligned;\nbarrier.cluster.wait.acquire.aligned;" ::: "memory");
    return;
  }

  uint32_t q[8];
  {
    const int lane = fresh_lane(), wg = warp >> 2, warp4 = warp & 3, c4 = lane & 3;
    if (warp == 15 && elect_one()) {
#pragma unroll
      for (int i = B_KVFULL; i < B_COUNT; i++) mbar_init(bar + 8 * i, bar_count(i, j, rank));
      sts_f2(sb + SM_TR, 0.f, 0.f);
      asm volatile("fence.mbarrier_init.release.cluster;" ::: "memory");
      fence_async_smem();
    }
    __syncwarp();
    if (warp == 15) asm volatile("bar.arrive 7, 96;" ::: "memory");
    const int row0 = 256 * r + 64 * wg + 16 * warp4 + (lane >> 2);
    float acc[48];
#pragma unroll 1
    for (int c = 0; c < 7; c++) {
      const uint64_t da = mkdesc(sb + (c & 3) * 32768 + wg * 8192, 16, 1024, 1);
      const uint64_t db = mkdesc(sb + SM_W + c * 12288, 4096, 512, 2);
      mbar_wait(sb, B_WQ + c);
      mbar_wait(sb, B_XFULL + c);
      if (c == 0) PMARK(wg, 1);
      wg_fence();
#pragma unroll
      for (int k = 0; k < 4; k++) mma_ss_n96_bf16_f32(acc, dadd(da, 32 * k), dadd(db, 1024 * k), (c | k) != 0);
      wg_commit();
      if (c == 0) asm volatile("barrier.cluster.wait.acquire.aligned;" ::: "memory");
      wg_wait<1>();
      if (c >= 1 && c <= 4 && lane == 0) {
        mbar_arrive(bar + 8 * (B_XREL + c - 1));
        if (c < 4) mbar_arrive_remote(mapa(bar + 8 * (B_XREL + c - 1), rank ^ 1));
      }
      if (c == 0) {
        {
          mbar_wait(sb, B_ST);
          uint32_t w[8];
          const uint32_t src = sb + st_stage + warp * 896 + (lane < 28 ? lane : 0) * 16;
          asm volatile("ld.shared.v4.u32 {%0, %1, %2, %3}, [%4];" : "=r"(w[0]), "=r"(w[1]), "=r"(w[2]), "=r"(w[3]) : "r"(src) : "memory");
          asm volatile("ld.shared.v4.u32 {%0, %1, %2, %3}, [%4];" : "=r"(w[4]), "=r"(w[5]), "=r"(w[6]), "=r"(w[7]) : "r"(src + 448) : "memory");
          const float piv = __shfl_sync(0xffffffffu, b_lo(w[0]), 0);
          if (lane == 0) mbar_arrive(bar + 8 * B_STDONE);
          float s1 = 0.f, s2 = 0.f;
    #pragma unroll
          for (int e = 0; e < 8; e++) {
            const float d0 = b_lo(w[e]) - piv, d1 = b_hi(w[e]) - piv;
            s1 += d0 + d1;
            s2 = fmaf(d0, d0, fmaf(d1, d1, s2));
          }
          if (lane >= 28) s1 = s2 = 0.f;
    #pragma unroll
          for (int o = 16; o; o >>= 1) {
            s1 += __shfl_xor_sync(0xffffffffu, s1, o);
            s2 += __shfl_xor_sync(0xffffffffu, s2, o);
          }
          const float m = s1 * (1.f / ND);
          if (lane == 0) st_tag2(g_st1 + 256 * r + 16 * h + warp, piv + m, rsqrtf(fmaxf(fmaf(-m, m, s2 * (1.f / ND)), 0.f) + 1e-5f), epoch(sb) & 1);
          PMARK(wg, 0);
        }
        if (tid < 384 && r < 7) {
          mbar_wait(sb, B_WQ + r);
          const uint32_t src = sb + SM_W + r * 12288 + ((tid % 48) >> 4) * 4096 + (tid / 48) * 512 + 4 * (tid & 3);
          float s0 = 0.f, s1 = 0.f;
#pragma unroll
          for (int k = 0; k < 8; k++) {
            const uint32_t w = lds_u32(src + k * 64 + ((((tid >> 2) & 3) ^ (k >> 1)) << 4));
            s0 += b_lo(w);
            s1 += b_hi(w);
          }
          sts_f2(sb + SM_RED + tid * 8, s0, s1);
        }
        asm volatile("bar.arrive 8, 544;" ::: "memory");
      }
    }
    const uint32_t par = epoch(sb) & 1;
    uint2 u0, u1;
    do {
      u0 = ld_rlx2(g_st1 + row0);
      u1 = ld_rlx2(g_st1 + row0 + 8);
    } while ((((u0.x ^ par) | (u0.y ^ par) | (u1.x ^ par) | (u1.y ^ par)) & 1u) != 0 && !timed_out(sb));
    const float m0 = __uint_as_float(u0.x), m1 = __uint_as_float(u1.x), r0 = __uint_as_float(u0.y), r1 = __uint_as_float(u1.y);
    PMARK(wg, 16);
    mbar_wait(sb, B_CS0);
    mbar_wait(sb, B_XREL + 3);
    PMARK(wg, 17);
    wg_wait<0>();
    pin(acc);
    PMARK(wg, 2);
    const bool padA = odd && c4 < 2, padB = !odd && c4 >= 2;
    float n0 = 0.f, n1 = 0.f, vm = 0.f;
    auto finish = [&](int n, float ra, float rb, uint32_t& p0, uint32_t& p1) {
      const float2 cs = lds_f2(sb + SM_CS0 + 32 * n + 8 * c4);
      if (((n & 3) == 0 && padA) || ((n & 3) == 3 && padB)) ra = rb = 0.f;
      float z0 = fmaf(-m0, cs.x, acc[4 * n]) * ra, z1 = fmaf(-m0, cs.y, acc[4 * n + 1]) * ra;
      float z2 = fmaf(-m1, cs.x, acc[4 * n + 2]) * rb, z3 = fmaf(-m1, cs.y, acc[4 * n + 3]) * rb;
      if (n < 8) {
        n0 = fmaf(z0, z0, fmaf(z1, z1, n0));
        n1 = fmaf(z2, z2, fmaf(z3, z3, n1));
      } else {
        vm = fmaxf(fmaxf(vm, fmaxf(fabsf(z0), fabsf(z1))), fmaxf(fabsf(z2), fabsf(z3)));
        if ((n == 8 && odd && c4 == 0) || (n == 11 && !odd && c4 == 2)) z0 = z2 = 1.f;
      }
      p0 = pack_h2(z0, z1);
      p1 = pack_h2(z2, z3);
    };
    uint32_t pk[16];
#pragma unroll
    for (int n = 4; n < 12; n++) finish(n, r0, r1, pk[2 * n - 8], pk[2 * n - 7]);
    const int srow = 64 * wg + 16 * warp4 + (lane & 7) + 8 * ((lane >> 3) & 1);
    const uint32_t sa = sb + SM_KV0 + (srow + (srow & 128)) * 64 + (((lane >> 4) ^ ((srow >> 1) & 3)) << 4);
#pragma unroll
    for (int n = 0; n < 4; n++) stsm4((sa ^ (32 * (n & 1))) + 8192 * (n >> 1), pk[4 * n], pk[4 * n + 1], pk[4 * n + 2], pk[4 * n + 3]);
    const int ka = __float_as_int(quad_sum(n0)), kb = __float_as_int(quad_sum(n1));
    const int km = __reduce_max_sync(0xffffffffu, max(ka & 0x7fffffff, kb & 0x7fffffff));
    const int vmx = __reduce_max_sync(0xffffffffu, __float_as_int(vm));
    if (lane == 0) {
      asm volatile("red.shared.max.s32 [%0], %1;" ::"r"(sb + SM_TR), "r"(km) : "memory");
      asm volatile("red.shared.max.s32 [%0], %1;" ::"r"(sb + SM_TR + 4), "r"(vmx) : "memory");
    }
    fence_async_smem();
    __syncwarp();
    if (lane == 0) mbar_arrive(bar + 8 * (B_KVFULL + (wg >> 1)));
    n0 = n1 = 0.f;
#pragma unroll
    for (int n = 0; n < 4; n++) finish(n, r0 * 0.27264365f, r1 * 0.27264365f, q[2 * n], q[2 * n + 1]);
    const int qa = __float_as_int(quad_sum(n0)), qb = __float_as_int(quad_sum(n1));
    sts_u32(sb + SM_RED + 4 * tid, max(qa & 0x7fffffff, qb & 0x7fffffff));
    PMARK(wg, 3);
  }
  asm volatile("setmaxnreg.inc.sync.aligned.u32 112;");
  {
    float o[16];
    uint32_t sc[32], oh[8];
#pragma unroll
    for (int i = 0; i < 16; i++) o[i] = 0.f;
    uint64_t kd = mkdesc(sb + SM_KV0, 16, 512, 2);
    mbar_wait(sb, B_KVFULL);
    pin(q);
    wg_fence();
    mma_rs_n128_f16_f16<0>(sc, q[0], q[1], q[2], q[3], kd);
    mma_rs_n128_f16_f16<1>(sc, q[4], q[5], q[6], q[7], dadd(kd, 32));
    wg_commit();
    wg_wait<0>();
    pin(sc);
    PMARK(threadIdx.x >> 7, 4);
    if (ATT_WAIT == 4) mbar_wait(sb, B_KVFULL + 1);
    uint32_t nslot = 0;
    const int ring = __shfl_sync(0xffffffffu, fresh_tid() >> 7, 0);
    if (ATT_SYNC > 0 && ring == 3) asm volatile("bar.arrive 11, 256;" ::: "memory");
#pragma unroll 1
    for (int blk = 0; blk < 8; blk++) {
      attn_tile<1>(sc, oh, q, dadd(kd, 16384), dadd(kd, 8192), sb, B_KVFULL + 2 * blk + 1, ring);
      const uint64_t kn = blk < 7 ? mkdesc(sb + nslot, 16, 512, 2) : kd;
      nslot = nslot == 65536 ? 0 : nslot + 32768;
      attn_tile<0>(sc, oh, q, kn, dadd(kd, 16384 + 8192), sb, B_KVFULL + (blk < 7 ? 2 * blk + 2 : 15), ring);
      if (fresh_lane() == 0) mbar_arrive(bar + 8 * (B_KVREL + blk));
#pragma unroll
      for (int i = 0; i < 8; i++) {
        const float2 f = __half22float2(*reinterpret_cast<const __half2*>(&oh[i]));
        o[2 * i] += f.x;
        o[2 * i + 1] += f.y;
      }
      kd = kn;
    }
    if (ATT_SYNC > 0 && ring == 0) asm volatile("bar.sync 11, 256;" ::: "memory");
    const int tid = fresh_tid(), lane = tid & 31, wg = tid >> 7, warp4 = (tid >> 5) & 3, c4 = lane & 3;
    const float qn2 = __uint_as_float(lds_u32(sb + SM_RED + 4 * tid));
    PMARK(wg, 5);
    if (lane == 0) {
      mbar_arrive(bar + 8 * B_AFREE1);
      mbar_arrive_remote(mapa(bar + 8 * B_AFREE1, rank ^ 1));
    }
    const int src = (lane & 28) | (odd ? 0 : 2);
    const float l0 = __shfl_sync(0xffffffffu, odd ? o[0] : o[12], src), l1 = __shfl_sync(0xffffffffu, odd ? o[2] : o[14], src);
    const float2 tr = lds_f2(sb + SM_TR + 16 * (lane & 7));
    const float kn2 = __int_as_float(__reduce_max_sync(0xffffffffu, __float_as_int(tr.x)));
    const float vmx = __int_as_float(__reduce_max_sync(0xffffffffu, __float_as_int(tr.y)));
    float om = 0.f;
#pragma unroll
    for (int i = 0; i < 16; i++) om += fabsf(o[i]);
    const float lm = fminf(l0, l1);
    const bool ok = qn2 * kn2 <= 950.f && qn2 <= 1e6f && kn2 <= 1e6f && vmx <= 3e4f && vmx >= 2.5e-4f && om <= 1e30f && lm >= 0.03125f &&
                    lm * vmx >= 0.00390625f;
    const uint32_t stage = sb + SM_KV0 + wg * 4096;
    if (__all_sync(0xffffffffu, ok)) {
      const float i0 = __frcp_rn(l0), i1 = __frcp_rn(l1);
      uint32_t op[8];
#pragma unroll
      for (int n = 0; n < 4; n++) {
        const bool pad = (n == 0 && odd && c4 < 2) || (n == 3 && !odd && c4 >= 2);
        op[2 * n] = pad ? 0u : pack_b2(o[4 * n] * i0, o[4 * n + 1] * i0);
        op[2 * n + 1] = pad ? 0u : pack_b2(o[4 * n + 2] * i1, o[4 * n + 3] * i1);
      }
      const int srow = 16 * warp4 + (lane & 7) + 8 * ((lane >> 3) & 1);
      const uint32_t sa = stage + srow * 64 + (((lane >> 4) ^ ((srow >> 1) & 3)) << 4);
      stsm4(sa, op[0], op[1], op[2], op[3]);
      stsm4(sa ^ 32, op[4], op[5], op[6], op[7]);
    } else {
      attention_exact(x, wqkv, h, 256 * r + 64 * wg + 16 * warp4, stage + warp4 * 1024);
    }
    fence_async_smem();
    PMARK(wg, 18);
    bar_sync(2 + wg, 128);
    if (warp4 == 0 && elect_one()) {
      const int og = 2 * r + (wg >> 1);
      bulk_s2g(g_O + (size_t)(og * 16 + h) * 8192 + (wg & 1) * 4096, stage, 4096);
      bulk_commit_wait();
      fence_async_all();
      red_add(g_flagO + (og * 8 + (h >> 1)) * 8);
      mbar_arrive(bar + 8 * B_AFREE1);
      mbar_arrive_remote(mapa(bar + 8 * B_AFREE1, rank ^ 1));
    }
    __syncwarp();
    PMARK(wg, 6);
  }
  phase_c(sb, g, j, x, w1, out PROF_ARG);
  asm volatile("barrier.cluster.wait.acquire.aligned;" ::: "memory");
}

typedef CUresult (*EncodeFn)(CUtensorMap*, CUtensorMapDataType, cuuint32_t, void*, const cuuint64_t*, const cuuint64_t*, const cuuint32_t*,
                             const cuuint32_t*, CUtensorMapInterleave, CUtensorMapSwizzle, CUtensorMapL2promotion, CUtensorMapFloatOOBfill);

void make2d(EncodeFn enc, CUtensorMap* tm, const void* p, int rows, int cols, int box_rows) {
  cuuint64_t dims[2] = {(cuuint64_t)cols, (cuuint64_t)rows}, str[1] = {(cuuint64_t)cols * 2};
  cuuint32_t box[2] = {64, (cuuint32_t)box_rows}, es[2] = {1, 1};
  enc(tm, CU_TENSOR_MAP_DATA_TYPE_BFLOAT16, 2, const_cast<void*>(p), dims, str, box, es, CU_TENSOR_MAP_INTERLEAVE_NONE,
      CU_TENSOR_MAP_SWIZZLE_128B, CU_TENSOR_MAP_L2_PROMOTION_L2_128B, CU_TENSOR_MAP_FLOAT_OOB_FILL_NONE);
}

}

extern "C" void kernel_launch(void* const* d_in, const int* in_sizes, int n_in, void* d_out, int out_size) {
  const __nv_bfloat16* x = (const __nv_bfloat16*)d_in[0];
  const __nv_bfloat16* wqkv = (const __nv_bfloat16*)d_in[1];
  const __nv_bfloat16* wo = (const __nv_bfloat16*)d_in[2];
  const __nv_bfloat16* w1 = (const __nv_bfloat16*)d_in[4];
  const __nv_bfloat16* w2 = (const __nv_bfloat16*)d_in[5];
  void* fn = nullptr;
  cudaDriverEntryPointQueryResult qr;
  cudaGetDriverEntryPoint("cuTensorMapEncodeTiled", &fn, cudaEnableDefault, &qr);
  EncodeFn enc = (EncodeFn)fn;
  CUtensorMap tmX, tmWq, tmWo, tmW1, tmW2;
  make2d(enc, &tmX, x, NS, ND, 128);
  make2d(enc, &tmWo, wo, ND, ND, 64);
  make2d(enc, &tmW1, w1, ND, NF, 64);
  make2d(enc, &tmW2, w2, NF, ND, 64);
  {
    cuuint64_t dims[3] = {ND, ND, 3}, str[2] = {3 * ND * 2, ND * 2};
    cuuint32_t box[3] = {32, 64, 3}, es[3] = {1, 1, 1};
    enc(&tmWq, CU_TENSOR_MAP_DATA_TYPE_BFLOAT16, 3, const_cast<__nv_bfloat16*>(wqkv), dims, str, box, es, CU_TENSOR_MAP_INTERLEAVE_NONE,
        CU_TENSOR_MAP_SWIZZLE_64B, CU_TENSOR_MAP_L2_PROMOTION_L2_128B, CU_TENSOR_MAP_FLOAT_OOB_FILL_NONE);
  }
  cudaFuncSetAttribute(fused_block_kernel, cudaFuncAttributeMaxDynamicSharedMemorySize, SM_TOTAL);
  fused_block_kernel<<<128, NTHREADS, SM_TOTAL, cudaStreamPerThread>>>(tmX, tmWq, tmWo, tmW1, tmW2, x, wqkv, wo, w1, w2,
                                                                         (__nv_bfloat16*)d_out);
}
```

```cpp
#include <cuda_runtime.h>
#include <cuda.h>
#include <cuda_bf16.h>
#include <cuda_fp16.h>
#include <stdint.h>

namespace {

constexpr int NS = 2048, ND = 448, NF = 1792;
constexpr int NTHREADS = 640;
#define POLY_MASK 0x5AD6B5ADu
#define ST_POS 0
#define ST_USE 1
#define ST_POLL 5
#define POLY_DEG 2

constexpr uint32_t SM_A = 0;
constexpr uint32_t SM_W = 131072;
constexpr uint32_t SM_KV0 = 98304;
constexpr uint32_t SM_BAR = 221184;
constexpr uint32_t SM_TR = SM_BAR + 1152;
constexpr uint32_t SM_CS0 = SM_TR + 128;
constexpr uint32_t SM_CS1 = SM_CS0 + 384;
constexpr uint32_t SM_RED = SM_CS1 + 1024;
constexpr uint32_t SM_ZERO = SM_RED + 2048;
constexpr uint32_t SM_ST = SM_ZERO;
constexpr uint32_t SM_EP = SM_ZERO + 2048;
constexpr uint32_t SM_PROF = SM_EP + 32;
constexpr uint32_t SM_TOTAL = SM_PROF + 1024 + 640;

enum : int {
  B_XFULL = 0, B_WQ = 7, B_XREL = 14, B_ST = 18, B_STDONE = 19, B_CS0 = 20  , B_KVFULL = 23  , B_KVREL = 39, B_AFREE1 = 47,
  B_OFULL = 48, B_WOFULL = 56, B_AFREE2 = 57, B_WODONE = 58, B_HFULL = 59, B_WFULL = 66, B_WREL = 94, B_GFULL = 122,
  B_AFREE3_L = 129, B_AFREE3_R = 130, B_CS1 = 131, B_OSTG = 132, B_WOREL = 133, B_TRDONE = 135, B_COUNT = 136
};

__device__ uint4 g_epoch[128];
__device__ __align__(128) unsigned char g_kv[16 * 8 * 32896];
__device__ uint32_t g_flagKV[16 * 8 * 8];
__device__ __align__(128) unsigned char g_O[16 * 16 * 8192];
__device__ uint32_t g_flagO[16 * 8 * 8];
__device__ __align__(128) unsigned char g_h[16 * 7 * 16384];
__device__ uint32_t g_flagH[16 * 8 * 8];
__device__ __align__(16) uint2 g_st1[NS];
__device__ uint2 g_st2[7 * NS];
__device__ uint2 g_cs1[8 * 16 * 128];
__device__ uint4 g_part[16 * 2 * 4 * 4 * 4 * 2 * 128];
#define PMARK(role, i) do {} while (0)
#define PDUMP(role) do {} while (0)
#define GMARK(i) do {} while (0)
#define PSTAGE(k, s) do {} while (0)
#define PROF_PARAM
#define PROF_ARG

__device__ __forceinline__ void wg_fence() { asm volatile("wgmma.fence.sync.aligned;" ::: "memory"); }
__device__ __forceinline__ void wg_commit() { asm volatile("wgmma.commit_group.sync.aligned;" ::: "memory"); }
template <int N> __device__ __forceinline__ void wg_wait() { asm volatile("wgmma.wait_group.sync.aligned %0;" ::"n"(N) : "memory"); }
template <int N> __device__ __forceinline__ void pin(float (&d)[N]) {
#pragma unroll
  for (int i = 0; i < N; i++) asm volatile("" : "+f"(d[i])::"memory");
}
template <int N> __device__ __forceinline__ void pin(uint32_t (&d)[N]) {
#pragma unroll
  for (int i = 0; i < N; i++) asm volatile("" : "+r"(d[i])::"memory");
}
__device__ __forceinline__ uint64_t mkdesc(uint32_t addr, uint32_t lbo, uint32_t sbo, uint32_t sw) {
  return ((uint64_t)((sbo >> 4) | (sw << 30)) << 32) | (uint64_t)(((addr & 0x3FFFFu) >> 4) | ((lbo >> 4) << 16));
}
__device__ __forceinline__ uint64_t dadd(uint64_t d, uint32_t off) { return d + (off >> 4); }
__device__ __forceinline__ bool timed_out(uint32_t sb) {
  uint32_t t0, t;
  asm volatile("ld.shared.u32 %0, [%1];" : "=r"(t0) : "r"(sb + SM_EP + 16));
  asm volatile("mov.u32 %0, %%clock;" : "=r"(t));
  return (int)(t - t0) < 0;
}
__device__ __forceinline__ void mbar_init(uint32_t b, uint32_t cnt) { asm volatile("mbarrier.init.shared::cta.b64 [%0], %1;" ::"r"(b), "r"(cnt) : "memory"); }
__device__ __forceinline__ uint32_t bar_count(int i, int j, int rank) {
  if (i >= B_XREL && i < B_XREL + 3) return 32;
  if (i == B_AFREE1) return 38;
  if (i == B_STDONE) return 2;
  if (i == B_XREL + 3 || i == B_TRDONE || (i >= B_KVREL && i < B_KVREL + 8) || i == B_AFREE2 || i == B_AFREE3_L || i == B_AFREE3_R) return 16;
    if (i == B_WODONE) return j < 7 ? 10 : 8;
  if (i == B_OSTG || i == B_WOREL || i == B_WOREL + 1 || i == B_KVFULL || i == B_KVFULL + 1 || (i >= B_WREL && i < B_WREL + 28)) return 8;
  if (i == B_HFULL + j && j < 7) return 2;
  if (i == B_CS1) return 6;
  if (i >= B_GFULL && i < B_GFULL + 7 && ((i - B_GFULL >= 4) == (rank == 1))) return 8;
  return 1;
}
__device__ __forceinline__ void mbar_expect(uint32_t b, uint32_t bytes) {
  asm volatile("mbarrier.arrive.expect_tx.shared::cta.b64 _, [%0], %1;" ::"r"(b), "r"(bytes) : "memory");
}
__device__ __forceinline__ void mbar_arrive(uint32_t b) { asm volatile("mbarrier.arrive.shared::cta.b64 _, [%0];" ::"r"(b) : "memory"); }
__device__ __forceinline__ uint32_t mapa(uint32_t a, uint32_t rank) {
  uint32_t r;
  asm("mapa.shared::cluster.u32 %0, %1, %2;" : "=r"(r) : "r"(a), "r"(rank));
  return r;
}
__device__ __forceinline__ void mbar_arrive_remote(uint32_t rb) {
  asm volatile("mbarrier.arrive.shared::cluster.b64 _, [%0];" ::"r"(rb) : "memory");
}
__device__ __forceinline__ void mbar_wait_addr(uint32_t sb, uint32_t addr) {
  asm volatile(
      "{\n.reg .pred p;\n.reg .u32 t0, t1;\n"
      "W_LOOP:\n"
      "mbarrier.try_wait.parity.shared::cta.b64 p, [%0], 0, 20000;\n"
      "@p bra W_DONE;\n"
      "ld.shared.u32 t0, [%1];\nmov.u32 t1, %%clock;\nsub.u32 t1, t1, t0;\nsetp.ge.s32 p, t1, 0;\n"
      "@p bra W_LOOP;\n"
      "W_DONE:\n}"
      ::"r"(addr), "r"(sb + SM_EP + 16) : "memory");
}
__device__ __forceinline__ uint32_t mbar_test(uint32_t sb, int idx) {
  uint32_t ok;
  asm volatile("{\n.reg .pred p;\nmbarrier.test_wait.parity.shared::cta.b64 p, [%1], 0;\nselp.u32 %0, 1, 0, p;\n}"
               : "=r"(ok) : "r"(sb + SM_BAR + 8 * idx) : "memory");
  return ok;
}
__device__ __forceinline__ void mbar_wait(uint32_t sb, int idx) { mbar_wait_addr(sb, sb + SM_BAR + 8 * idx); }
__device__ __forceinline__ void bar_sync(int id, int n) { asm volatile("bar.sync %0, %1;" ::"r"(id), "r"(n) : "memory"); }
__device__ __forceinline__ void fence_async_smem() { asm volatile("fence.proxy.async.shared::cta;" ::: "memory"); }
__device__ __forceinline__ void fence_async_all() { asm volatile("fence.proxy.async.global;" ::: "memory"); }
__device__ __forceinline__ void tma2d(uint32_t dst, const CUtensorMap* tm, int c0, int c1, uint32_t bar) {
  asm volatile("cp.async.bulk.tensor.2d.shared::cluster.global.mbarrier::complete_tx::bytes [%0], [%1, {%3, %4}], [%2];"
               ::"r"(dst), "l"(tm), "r"(bar), "r"(c0), "r"(c1) : "memory");
}
__device__ __forceinline__ void tma2d_mc(uint32_t dst, const CUtensorMap* tm, int c0, int c1, uint32_t bar) {
  asm volatile("cp.async.bulk.tensor.2d.shared::cluster.global.mbarrier::complete_tx::bytes.multicast::cluster [%0], [%1, {%3, %4}], [%2], %5;"
               ::"r"(dst), "l"(tm), "r"(bar), "r"(c0), "r"(c1), "h"((uint16_t)3) : "memory");
}
__device__ __forceinline__ void tma3d(uint32_t dst, const CUtensorMap* tm, int c0, int c1, int c2, uint32_t bar) {
  asm volatile("cp.async.bulk.tensor.3d.shared::cluster.global.mbarrier::complete_tx::bytes [%0], [%1, {%3, %4, %5}], [%2];"
               ::"r"(dst), "l"(tm), "r"(bar), "r"(c0), "r"(c1), "r"(c2) : "memory");
}
__device__ __forceinline__ void bulk_g2s(uint32_t dst, const void* src, uint32_t bytes, uint32_t bar) {
  asm volatile("cp.async.bulk.shared::cluster.global.mbarrier::complete_tx::bytes [%0], [%1], %2, [%3];"
               ::"r"(dst), "l"(src), "r"(bytes), "r"(bar) : "memory");
}
__device__ __forceinline__ void bulk_g2s_mc(uint32_t dst, const void* src, uint32_t bytes, uint32_t bar) {
  asm volatile("cp.async.bulk.shared::cluster.global.mbarrier::complete_tx::bytes.multicast::cluster [%0], [%1], %2, [%3], %4;"
               ::"r"(dst), "l"(src), "r"(bytes), "r"(bar), "h"((uint16_t)3) : "memory");
}
__device__ __forceinline__ void bulk_s2g(void* dst, uint32_t src, uint32_t bytes) {
  asm volatile("cp.async.bulk.global.shared::cta.bulk_group [%0], [%1], %2;" ::"l"(dst), "r"(src), "r"(bytes) : "memory");
}
__device__ __forceinline__ void bulk_s2peer(uint32_t rdst, uint32_t src, uint32_t bytes, uint32_t rbar) {
  asm volatile("cp.async.bulk.shared::cluster.shared::cta.mbarrier::complete_tx::bytes [%0], [%1], %2, [%3];"
               ::"r"(rdst), "r"(src), "r"(bytes), "r"(rbar) : "memory");
}
__device__ __forceinline__ void bulk_commit_wait() {
  asm volatile("cp.async.bulk.commit_group;\ncp.async.bulk.wait_group 0;" ::: "memory");
}
__device__ __forceinline__ void l2_prefetch(const void* p, uint32_t bytes) {
  asm volatile("cp.async.bulk.prefetch.L2.global [%0], %1;" ::"l"(p), "r"(bytes) : "memory");
}
__device__ __forceinline__ uint32_t ld_flag(const uint32_t* p) {
  uint32_t v;
  asm volatile("ld.acquire.gpu.global.u32 %0, [%1];" : "=r"(v) : "l"(p) : "memory");
  return v;
}
__device__ __forceinline__ void red_add(uint32_t* p) { asm volatile("red.relaxed.gpu.global.add.u32 [%0], 1;" ::"l"(p) : "memory"); }
__device__ __forceinline__ uint32_t tagw(float v, uint32_t par) { return (__float_as_uint(v) & ~1u) | par; }
__device__ __forceinline__ void st_tag2(uint2* p, float a, float b, uint32_t par) {
  asm volatile("st.relaxed.gpu.global.v2.u32 [%0], {%1, %2};" ::"l"(p), "r"(tagw(a, par)), "r"(tagw(b, par)) : "memory");
}
__device__ __forceinline__ uint2 ld_rlx2(const uint2* p) {
  uint2 v;
  asm volatile("ld.relaxed.gpu.global.v2.u32 {%0, %1}, [%2];" : "=r"(v.x), "=r"(v.y) : "l"(p) : "memory");
  return v;
}
__device__ __forceinline__ void st_rec_if(bool p, uint4* q, uint32_t a, uint32_t b, uint32_t c, uint32_t d) {
  asm volatile("{\n.reg .b128 v;\n.reg .b64 lo, hi;\n.reg .pred p;\nsetp.ne.u32 p, %5, 0;\nmov.b64 lo, {%1, %2};\nmov.b64 hi, {%3, %4};\n"
               "mov.b128 v, {lo, hi};\n@p st.relaxed.gpu.global.b128 [%0], v;\n}" ::"l"(q), "r"(a), "r"(b), "r"(c), "r"(d), "r"((uint32_t)p) : "memory");
}
__device__ __forceinline__ uint4 ld_rec(const uint4* p) {
  uint4 v;
  asm volatile("{\n.reg .b128 v;\n.reg .b64 lo, hi;\nld.relaxed.gpu.global.b128 v, [%4];\nmov.b128 {lo, hi}, v;\n"
               "mov.b64 {%0, %1}, lo;\nmov.b64 {%2, %3}, hi;\n}" : "=r"(v.x), "=r"(v.y), "=r"(v.z), "=r"(v.w) : "l"(p) : "memory");
  return v;
}
__device__ __forceinline__ uint32_t pack_h2(float lo, float hi) {
  uint32_t r;
  asm("cvt.rn.f16x2.f32 %0, %1, %2;" : "=r"(r) : "f"(hi), "f"(lo));
  return r;
}
__device__ __forceinline__ uint32_t pack_b2(float lo, float hi) {
  uint32_t r;
  asm("cvt.rn.bf16x2.f32 %0, %1, %2;" : "=r"(r) : "f"(hi), "f"(lo));
  return r;
}
__device__ __forceinline__ float b_lo(uint32_t v) { return __uint_as_float(v << 16); }
__device__ __forceinline__ float b_hi(uint32_t v) { return __uint_as_float(v & 0xFFFF0000u); }
__device__ __forceinline__ void stsm4(uint32_t addr, uint32_t a, uint32_t b, uint32_t c, uint32_t d) {
  asm volatile("stmatrix.sync.aligned.m8n8.x4.shared.b16 [%0], {%1, %2, %3, %4};" ::"r"(addr), "r"(a), "r"(b), "r"(c), "r"(d) : "memory");
}
__device__ __forceinline__ uint4 lds_u4(uint32_t a) {
  uint4 v;
  asm volatile("ld.shared.v4.u32 {%0, %1, %2, %3}, [%4];" : "=r"(v.x), "=r"(v.y), "=r"(v.z), "=r"(v.w) : "r"(a) : "memory");
  return v;
}
__device__ __forceinline__ float2 lds_f2(uint32_t a) {
  float2 v;
  asm volatile("ld.shared.v2.f32 {%0, %1}, [%2];" : "=f"(v.x), "=f"(v.y) : "r"(a) : "memory");
  return v;
}
__device__ __forceinline__ uint32_t lds_u32(uint32_t a) {
  uint32_t v;
  asm volatile("ld.shared.u32 %0, [%1];" : "=r"(v) : "r"(a) : "memory");
  return v;
}
__device__ __forceinline__ uint32_t epoch(uint32_t sb) { return lds_u32(sb + SM_EP) + 1; }
__device__ __forceinline__ void sts_f2(uint32_t a, float x, float y) { asm volatile("st.shared.v2.f32 [%0], {%1, %2};" ::"r"(a), "f"(x), "f"(y) : "memory"); }
__device__ __forceinline__ float quad_sum(float v) {
  v += __shfl_xor_sync(0xffffffffu, v, 1);
  return v + __shfl_xor_sync(0xffffffffu, v, 2);
}

__device__ __forceinline__ int fresh_tid() {
  int t;
  asm volatile("mov.u32 %0, %%tid.x;" : "=r"(t));
  return t;
}
__device__ __forceinline__ int uniform_wg() { return __shfl_sync(0xffffffffu, fresh_tid() >> 7, 0); }
__device__ __forceinline__ int fresh_lane() {
  int t;
  asm volatile("mov.u32 %0, %%laneid;" : "=r"(t));
  return t;
}
__device__ __forceinline__ bool elect_one() {
  uint32_t p;
  asm volatile("{\n.reg .pred p;\nelect.sync _|p, 0xffffffff;\nselp.u32 %0, 1, 0, p;\n}" : "=r"(p));
  return p;
}
__device__ __forceinline__ void sts_u32(uint32_t a, uint32_t v) { asm volatile("st.shared.u32 [%0], %1;" ::"r"(a), "r"(v) : "memory"); }

__device__ __forceinline__ void mma_ss_n96_bf16_f32(float (&d)[48], uint64_t da, uint64_t db, int acc) {
  asm volatile(
      "{\n.reg .pred p;\nsetp.ne.b32 p, %50, 0;\n"
      "wgmma.mma_async.sync.aligned.m64n96k16.f32.bf16.bf16 {"
      "%0, %1, %2, %3, %4, %5, %6, %7, %8, %9, %10, %11, %12, %13, %14, %15, %16, %17, %18, %19, %20, %21, %22, "
      "%23, %24, %25, %26, %27, %28, %29, %30, %31, %32, %33, %34, %35, %36, %37, %38, %39, %40, %41, %42, %43, "
      "%44, %45, %46, %47"
      "}, %48, %49, p, 1, 1, 0, 1;\n}\n"
      : "+f"(d[0]), "+f"(d[1]), "+f"(d[2]), "+f"(d[3]), "+f"(d[4]), "+f"(d[5]), "+f"(d[6]), "+f"(d[7]),
        "+f"(d[8]), "+f"(d[9]), "+f"(d[10]), "+f"(d[11]), "+f"(d[12]), "+f"(d[13]), "+f"(d[14]), "+f"(d[15]),
        "+f"(d[16]), "+f"(d[17]), "+f"(d[18]), "+f"(d[19]), "+f"(d[20]), "+f"(d[21]), "+f"(d[22]), "+f"(d[23]),
        "+f"(d[24]), "+f"(d[25]), "+f"(d[26]), "+f"(d[27]), "+f"(d[28]), "+f"(d[29]), "+f"(d[30]), "+f"(d[31]),
        "+f"(d[32]), "+f"(d[33]), "+f"(d[34]), "+f"(d[35]), "+f"(d[36]), "+f"(d[37]), "+f"(d[38]), "+f"(d[39]),
        "+f"(d[40]), "+f"(d[41]), "+f"(d[42]), "+f"(d[43]), "+f"(d[44]), "+f"(d[45]), "+f"(d[46]), "+f"(d[47])
      : "l"(da), "l"(db), "r"(acc));
}
__device__ __forceinline__ void mma_ss_n64_bf16_f32(float (&d)[32], uint64_t da, uint64_t db, int acc) {
  asm volatile(
      "{\n.reg .pred p;\nsetp.ne.b32 p, %34, 0;\n"
      "wgmma.mma_async.sync.aligned.m64n64k16.f32.bf16.bf16 {"
      "%0, %1, %2, %3, %4, %5, %6, %7, %8, %9, %10, %11, %12, %13, %14, %15, %16, %17, %18, %19, %20, %21, %22, "
      "%23, %24, %25, %26, %27, %28, %29, %30, %31"
      "}, %32, %33, p, 1, 1, 0, 1;\n}\n"
      : "+f"(d[0]), "+f"(d[1]), "+f"(d[2]), "+f"(d[3]), "+f"(d[4]), "+f"(d[5]), "+f"(d[6]), "+f"(d[7]),
        "+f"(d[8]), "+f"(d[9]), "+f"(d[10]), "+f"(d[11]), "+f"(d[12]), "+f"(d[13]), "+f"(d[14]), "+f"(d[15]),
        "+f"(d[16]), "+f"(d[17]), "+f"(d[18]), "+f"(d[19]), "+f"(d[20]), "+f"(d[21]), "+f"(d[22]), "+f"(d[23]),
        "+f"(d[24]), "+f"(d[25]), "+f"(d[26]), "+f"(d[27]), "+f"(d[28]), "+f"(d[29]), "+f"(d[30]), "+f"(d[31])
      : "l"(da), "l"(db), "r"(acc));
}
__device__ __forceinline__ void mma_ss_n128_bf16_f32(float (&d)[64], uint64_t da, uint64_t db, int acc) {
  asm volatile(
      "{\n.reg .pred p;\nsetp.ne.b32 p, %66, 0;\n"
      "wgmma.mma_async.sync.aligned.m64n128k16.f32.bf16.bf16 {"
      "%0, %1, %2, %3, %4, %5, %6, %7, %8, %9, %10, %11, %12, %13, %14, %15, %16, %17, %18, %19, %20, %21, %22, "
      "%23, %24, %25, %26, %27, %28, %29, %30, %31, %32, %33, %34, %35, %36, %37, %38, %39, %40, %41, %42, %43, "
      "%44, %45, %46, %47, %48, %49, %50, %51, %52, %53, %54, %55, %56, %57, %58, %59, %60, %61, %62, %63"
      "}, %64, %65, p, 1, 1, 0, 1;\n}\n"
      : "+f"(d[0]), "+f"(d[1]), "+f"(d[2]), "+f"(d[3]), "+f"(d[4]), "+f"(d[5]), "+f"(d[6]), "+f"(d[7]),
        "+f"(d[8]), "+f"(d[9]), "+f"(d[10]), "+f"(d[11]), "+f"(d[12]), "+f"(d[13]), "+f"(d[14]), "+f"(d[15]),
        "+f"(d[16]), "+f"(d[17]), "+f"(d[18]), "+f"(d[19]), "+f"(d[20]), "+f"(d[21]), "+f"(d[22]), "+f"(d[23]),
        "+f"(d[24]), "+f"(d[25]), "+f"(d[26]), "+f"(d[27]), "+f"(d[28]), "+f"(d[29]), "+f"(d[30]), "+f"(d[31]),
        "+f"(d[32]), "+f"(d[33]), "+f"(d[34]), "+f"(d[35]), "+f"(d[36]), "+f"(d[37]), "+f"(d[38]), "+f"(d[39]),
        "+f"(d[40]), "+f"(d[41]), "+f"(d[42]), "+f"(d[43]), "+f"(d[44]), "+f"(d[45]), "+f"(d[46]), "+f"(d[47]),
        "+f"(d[48]), "+f"(d[49]), "+f"(d[50]), "+f"(d[51]), "+f"(d[52]), "+f"(d[53]), "+f"(d[54]), "+f"(d[55]),
        "+f"(d[56]), "+f"(d[57]), "+f"(d[58]), "+f"(d[59]), "+f"(d[60]), "+f"(d[61]), "+f"(d[62]), "+f"(d[63])
      : "l"(da), "l"(db), "r"(acc));
}
template <int ACC>
__device__ __forceinline__ void mma_rs_n128_f16_f16(uint32_t (&d)[32], uint32_t a0, uint32_t a1, uint32_t a2, uint32_t a3, uint64_t db) {
  asm volatile(
      "{\n.reg .pred p;\nsetp.ne.b32 p, %37, 0;\n"
      "wgmma.mma_async.sync.aligned.m64n128k16.f16.f16.f16 {"
      "%0, %1, %2, %3, %4, %5, %6, %7, %8, %9, %10, %11, %12, %13, %14, %15, %16, %17, %18, %19, %20, %21, %22, "
      "%23, %24, %25, %26, %27, %28, %29, %30, %31"
      "}, {%32, %33, %34, %35}, %36, p, 1, 1, 0;\n}\n"
      : "+r"(d[0]), "+r"(d[1]), "+r"(d[2]), "+r"(d[3]), "+r"(d[4]), "+r"(d[5]), "+r"(d[6]), "+r"(d[7]),
        "+r"(d[8]), "+r"(d[9]), "+r"(d[10]), "+r"(d[11]), "+r"(d[12]), "+r"(d[13]), "+r"(d[14]), "+r"(d[15]),
        "+r"(d[16]), "+r"(d[17]), "+r"(d[18]), "+r"(d[19]), "+r"(d[20]), "+r"(d[21]), "+r"(d[22]), "+r"(d[23]),
        "+r"(d[24]), "+r"(d[25]), "+r"(d[26]), "+r"(d[27]), "+r"(d[28]), "+r"(d[29]), "+r"(d[30]), "+r"(d[31])
      : "r"(a0), "r"(a1), "r"(a2), "r"(a3), "l"(db), "n"(ACC));
}
template <int ACC>
__device__ __forceinline__ void mma_rs_n32_f16_f16(uint32_t (&d)[8], uint32_t a0, uint32_t a1, uint32_t a2, uint32_t a3, uint64_t db) {
  asm volatile(
      "{\n.reg .pred p;\nsetp.ne.b32 p, %13, 0;\n"
      "wgmma.mma_async.sync.aligned.m64n32k16.f16.f16.f16 {"
      "%0, %1, %2, %3, %4, %5, %6, %7"
      "}, {%8, %9, %10, %11}, %12, p, 1, 1, 1;\n}\n"
      : "+r"(d[0]), "+r"(d[1]), "+r"(d[2]), "+r"(d[3]), "+r"(d[4]), "+r"(d[5]), "+r"(d[6]), "+r"(d[7])
      : "r"(a0), "r"(a1), "r"(a2), "r"(a3), "l"(db), "n"(ACC));
}
__device__ __forceinline__ void mma_ss_n64w_bf16_f32(float (&d)[64], uint64_t da, uint64_t db, int acc) {
  asm volatile(
      "{\n.reg .pred p;\nsetp.ne.b32 p, %34, 0;\n"
      "wgmma.mma_async.sync.aligned.m64n64k16.f32.bf16.bf16 {"
      "%0, %1, %2, %3, %4, %5, %6, %7, %8, %9, %10, %11, %12, %13, %14, %15, %16, %17, %18, %19, %20, %21, %22, "
      "%23, %24, %25, %26, %27, %28, %29, %30, %31"
      "}, %32, %33, p, 1, 1, 0, 1;\n}\n"
      : "+f"(d[0]), "+f"(d[1]), "+f"(d[2]), "+f"(d[3]), "+f"(d[4]), "+f"(d[5]), "+f"(d[6]), "+f"(d[7]),
        "+f"(d[8]), "+f"(d[9]), "+f"(d[10]), "+f"(d[11]), "+f"(d[12]), "+f"(d[13]), "+f"(d[14]), "+f"(d[15]),
        "+f"(d[16]), "+f"(d[17]), "+f"(d[18]), "+f"(d[19]), "+f"(d[20]), "+f"(d[21]), "+f"(d[22]), "+f"(d[23]),
        "+f"(d[24]), "+f"(d[25]), "+f"(d[26]), "+f"(d[27]), "+f"(d[28]), "+f"(d[29]), "+f"(d[30]), "+f"(d[31])
      : "l"(da), "l"(db), "r"(acc));
}
__device__ __forceinline__ void mma_rs_n32_f16_f16_rt(uint32_t (&d)[8], uint32_t a0, uint32_t a1, uint32_t a2, uint32_t a3, uint64_t db, int acc) {
  asm volatile(
      "{\n.reg .pred p;\nsetp.ne.b32 p, %13, 0;\n"
      "wgmma.mma_async.sync.aligned.m64n32k16.f16.f16.f16 {"
      "%0, %1, %2, %3, %4, %5, %6, %7"
      "}, {%8, %9, %10, %11}, %12, p, 1, 1, 1;\n}\n"
      : "+r"(d[0]), "+r"(d[1]), "+r"(d[2]), "+r"(d[3]), "+r"(d[4]), "+r"(d[5]), "+r"(d[6]), "+r"(d[7])
      : "r"(a0), "r"(a1), "r"(a2), "r"(a3), "l"(db), "r"(acc));
}

__device__ __forceinline__ uint32_t exp2_mufu(uint32_t x) {
  uint32_t r;
  asm("ex2.approx.f16x2 %0, %1;" : "=r"(r) : "r"(x));
  return r;
}
__device__ __forceinline__ uint32_t exp2_poly(uint32_t x) {
  uint32_t t, nn, f, q, e;
  asm("add.rn.f16x2 %0, %1, %2;" : "=r"(t) : "r"(x), "r"(0x66206620u));
  asm("sub.rn.f16x2 %0, %1, %2;" : "=r"(nn) : "r"(0x66206620u), "r"(t));
  asm("add.rn.f16x2 %0, %1, %2;" : "=r"(f) : "r"(x), "r"(nn));
  asm("fma.rn.f16x2 %0, %1, %2, %3;" : "=r"(q) : "r"(f), "r"(0xB3A4B3A4u), "r"(0xB9A0B9A0u));
  asm("fma.rn.f16x2 %0, %1, %2, %3;" : "=r"(q) : "r"(q), "r"(f), "r"(0xBC00BC00u));
  asm("mad.lo.u32 %0, %1, 1024, %2;" : "=r"(e) : "r"(t), "r"(0u - (0x198u << 16)));
  return __viaddmin_u16x2(q, e, 0x7C007C00u);
}

#define FLUSH_MASK 1
template <int FIRST>
__device__ __forceinline__ void attn_tile(uint32_t (&s)[32], uint32_t (&oh)[8], const uint32_t (&q)[8], uint64_t kd, uint64_t vd, uint32_t sb,
                                          int kbar, int keep) {
  uint32_t p[32];
  const uint32_t have = mbar_test(sb, kbar);
#pragma unroll
  for (int c = 0; c < 8; c += 4) {
#pragma unroll
    for (int g = 4 * c; g < 4 * c + 16; g++) p[g] = ((POLY_MASK >> g) & 1) ? exp2_poly(s[g]) : exp2_mufu(s[g]);
#pragma unroll
    for (int g = 4 * c; g < 4 * c + 16; g++) asm volatile("" : "+r"(p[g])::"memory");
    if (c == 4 && !have) mbar_wait(sb, kbar);
    wg_fence();
#pragma unroll
    for (int k = c; k < c + 4; k++) {
      if (FIRST && k == 0) mma_rs_n32_f16_f16_rt(oh, p[0], p[1], p[2], p[3], vd, keep);
      else mma_rs_n32_f16_f16<1>(oh, p[4 * k], p[4 * k + 1], p[4 * k + 2], p[4 * k + 3], vd);
      asm volatile("add.u64 %0, %0, 64;" : "+l"(vd));
    }
  }
  mma_rs_n128_f16_f16<0>(s, q[0], q[1], q[2], q[3], kd);
  mma_rs_n128_f16_f16<1>(s, q[4], q[5], q[6], q[7], dadd(kd, 32));
  wg_commit();
  wg_wait<0>();
  pin(p); pin(s); pin(oh);
}

__device__ __noinline__ void project_row(const __nv_bfloat16* __restrict__ xr, const __nv_bfloat16* __restrict__ w, float* dst) {
  float s = 0.f, v = 0.f;
#pragma unroll 8
  for (int k = 0; k < ND; k++) s += __bfloat162float(xr[k]);
  const float mu = s * (1.f / ND);
#pragma unroll 8
  for (int k = 0; k < ND; k++) { const float d = __bfloat162float(xr[k]) - mu; v += d * d; }
  const float rs = 1.f / sqrtf(v * (1.f / ND) + 1e-5f);
#pragma unroll 1
  for (int d0 = 0; d0 < 28; d0 += 4) {
    float a0 = 0.f, a1 = 0.f, a2 = 0.f, a3 = 0.f;
#pragma unroll 8
    for (int k = 0; k < ND; k++) {
      const float a = (__bfloat162float(xr[k]) - mu) * rs;
      const uint2 ww = *reinterpret_cast<const uint2*>(w + (size_t)k * (3 * ND) + d0);
      a0 = fmaf(a, b_lo(ww.x), a0); a1 = fmaf(a, b_hi(ww.x), a1); a2 = fmaf(a, b_lo(ww.y), a2); a3 = fmaf(a, b_hi(ww.y), a3);
    }
    dst[d0] = a0; dst[d0 + 1] = a1; dst[d0 + 2] = a2; dst[d0 + 3] = a3;
  }
}
__device__ __noinline__ void attention_exact(const __nv_bfloat16* __restrict__ x, const __nv_bfloat16* __restrict__ wqkv, int h, int row0,
                                             uint32_t stage) {
  const int lane = threadIdx.x & 31;
  float qv[28], kv[28], vv[28], o[28], m = -INFINITY, l = 0.f;
  project_row(x + (size_t)(row0 + (lane & 15)) * ND, wqkv + 28 * h, qv);
#pragma unroll 1
  for (int d = 0; d < 28; d++) o[d] = 0.f;
#pragma unroll 1
  for (int k0 = 0; k0 < NS; k0 += 32) {
    project_row(x + (size_t)(k0 + lane) * ND, wqkv + ND + 28 * h, kv);
    project_row(x + (size_t)(k0 + lane) * ND, wqkv + 2 * ND + 28 * h, vv);
#pragma unroll 1
    for (int t = 0; t < 32; t++) {
      float s = 0.f;
#pragma unroll 1
      for (int d = 0; d < 28; d++) s = fmaf(qv[d], __shfl_sync(0xffffffffu, kv[d], t), s);
      s *= 0.18898223650461362f;
      const float mn = fmaxf(m, s);
      const float corr = expf(m - mn), p = expf(s - mn);
      m = mn;
      l = l * corr + p;
#pragma unroll 1
      for (int d = 0; d < 28; d++) o[d] = o[d] * corr + p * __shfl_sync(0xffffffffu, vv[d], t);
    }
  }
  if (lane < 16) {
#pragma unroll 1
    for (int d = 0; d < 32; d += 2) {
      const int c = (d + 4 * (h & 1)) & 31;
      sts_u32(stage + lane * 64 + (((c >> 3) ^ ((lane >> 1) & 3)) << 4) + 2 * (c & 7), d < 28 ? pack_b2(o[d] / l, o[d + 1] / l) : 0u);
    }
  }
}

__device__ __forceinline__ uint32_t wslot(int s) { return ((uint32_t)(0x150E12101917ull >> (8 * (s % 6))) & 0xFF) * 8192; }
__device__ __forceinline__ uint32_t f2slot(int rank, int u) {
  const uint64_t t = u < 8 ? (rank ? 0x12101917150E1210ull : 0x1A171915130E1210ull) : (rank ? 0x000012101917150Eull : 0x0000191312150E10ull);
  return (uint32_t)(t >> (8 * (u & 7))) & 0xFF;
}
__device__ __forceinline__ uint32_t f2dep(int rank, int u) {
  const uint64_t t = u < 8 ? (rank ? 0x0F0E0D0C0B0A0908ull : 0x0D0C0D0B090A0908ull) : (rank ? 0x0000151413121110ull : 0x000013110F12100Eull);
  return (uint32_t)(t >> (8 * (u & 7))) & 0xFF;
}
__device__ __forceinline__ int wrap7(int c) { return c >= 7 ? c - 7 : c; }
__device__ __forceinline__ int hchunk(int j, int t) { return wrap7((j & 6) + (t < 2 && (j & 1) && j < 7 ? t ^ 1 : t)); }
__device__ __forceinline__ int f2stage(int rank, int pair, int t) {
  const int n = 4 - rank;
  return t < n ? 14 + 2 * t + pair : 14 + n + pair * (7 - n) + t;
}
__device__ __forceinline__ int stage_pair(int rank, int s) {
  const int n = 4 - rank;
  return s < 14 + 2 * n ? (s & 1) : (s - 21 >= n);
}

template <bool WIDE, bool SECOND>
__device__ __forceinline__ void ffn_loop(float (&acc)[64], uint32_t sb, int first, int rank, int pair, int half PROF_PARAM) {
  int prev = 0;
#pragma unroll 1
  for (int t = 0; t < 7; t++) {
    const int c = SECOND ? wrap7(first + t) : hchunk(first, t), s = SECOND ? f2stage(rank, pair, t) : 2 * t + pair;
    const uint64_t da = mkdesc(sb + SM_A + c * 16384 + half * 8192, 16, 1024, 1);
    const uint64_t db = mkdesc(sb + (SECOND ? f2slot(rank, s - 14) * 8192 : wslot(s)), 8192, 1024, 1);
    mbar_wait(sb, (SECOND ? B_GFULL : B_HFULL) + c);
    mbar_wait(sb, B_WFULL + s);
    wg_fence();
#pragma unroll
    for (int k = 0; k < 4; k++) {
      if (WIDE) mma_ss_n128_bf16_f32(acc, dadd(da, 32 * k), dadd(db, 2048 * k), (t | k) != 0);
      else mma_ss_n64w_bf16_f32(acc, dadd(da, 32 * k), dadd(db, 2048 * k), (t | k) != 0);
    }
    wg_commit();
    wg_wait<1>();
    if (t > 0 && elect_one()) mbar_arrive(sb + SM_BAR + 8 * (B_WREL + prev));
    prev = s;
  }
}

__device__ __forceinline__ void phase_c(uint32_t sb, int g, int j, const __nv_bfloat16* __restrict__ x, const __nv_bfloat16* __restrict__ w1,
                                        __nv_bfloat16* __restrict__ out PROF_PARAM) {
  const int tid = fresh_tid(), lane = tid & 31, wg = uniform_wg(), warp4 = (tid >> 5) & 3, c4 = lane & 3;
  const int rank = j & 1, ii = j >> 1, pair = wg >> 1, half = wg & 1;
  const uint32_t bar = sb + SM_BAR, par = epoch(sb) & 1;
  const int rl = 64 * half + 16 * warp4 + (lane >> 2);
  const int srow = 64 * half + 16 * warp4 + (lane & 7) + 8 * ((lane >> 3) & 1);
  const uint32_t soff = srow * 128 + (((lane >> 4) ^ (srow & 7)) << 4);
  if (pair == 0) {
    uint32_t hp[16];
    float acc[32];
    if (j < 7) {
      const __nv_bfloat16* xp = x + (size_t)(128 * g + rl) * ND + 64 * j + 2 * c4;
#pragma unroll
      for (int n = 0; n < 16; n++) hp[n] = __ldg(reinterpret_cast<const uint32_t*>(xp + (n & 1) * 8 * ND + 8 * (n >> 1)));
      mbar_wait(sb, B_WOFULL);
    }
#pragma unroll 1
    for (int c = 0; c < 8; c++) {
      const uint64_t da = mkdesc(sb + SM_A + c * 16384 + half * 4096, 16, 512, 2);
      const uint64_t db = mkdesc(sb + SM_W + c * 56 * 128, 8192, 1024, 1);
      mbar_wait(sb, B_OFULL + c);
      if (c == 0) PMARK(wg, 7);
      wg_fence();
#pragma unroll
      for (int k = 0; k < 4; k++)
        mma_ss_n64_bf16_f32(acc, dadd(da, 8192 * (k >> 1) + 32 * (k & 1)), dadd(db, 3072 * (k >> 1) + 2048 * (k & 1)), (c | k) != 0);
      wg_commit();
      wg_wait<1>();
      if ((c == 3 || c == 5) && elect_one()) mbar_arrive(bar + 8 * (B_WOREL + (c >> 2)));
    }
    wg_wait<0>();
    pin(acc);
    PMARK(wg, 8);
    if (lane == 0) {
      mbar_arrive(bar + 8 * B_WODONE);
      mbar_arrive(bar + 8 * B_AFREE2);
      mbar_arrive_remote(mapa(bar + 8 * B_AFREE2, rank ^ 1));
    }
    if (j < 7) {
#pragma unroll
      for (int n = 0; n < 16; n++) hp[n] = pack_b2(acc[2 * n] + b_lo(hp[n]), acc[2 * n + 1] + b_hi(hp[n]));
      bar_sync(6, 256);
#pragma unroll
      for (int n = 0; n < 4; n++) stsm4(sb + SM_A + j * 16384 + (soff ^ (32 * n)), hp[4 * n], hp[4 * n + 1], hp[4 * n + 2], hp[4 * n + 3]);
      fence_async_smem();
      bar_sync(2 + wg, 128);
      if (warp4 == 0 && elect_one()) {
        bulk_s2g(g_h + (size_t)(g * 7 + j) * 16384 + half * 8192, sb + SM_A + j * 16384 + half * 8192, 8192);
        mbar_arrive(bar + 8 * (B_HFULL + j));
        mbar_arrive(bar + 8 * B_WODONE);
        bulk_commit_wait();
        fence_async_all();
        red_add(g_flagH + (g * 8 + j) * 8);
      }
      if (warp4 == 1 && elect_one()) {
        mbar_wait(sb, B_AFREE2);
        const uint32_t src = sb + SM_A + j * 16384 + half * 8192;
        bulk_s2peer(mapa(src, rank ^ 1), src, 8192, mapa(bar + 8 * (B_HFULL + j), rank ^ 1));
      }
      __syncwarp();
      float s[2] = {0.f, 0.f}, v[2] = {0.f, 0.f};
#pragma unroll
      for (int n = 0; n < 16; n++) s[n & 1] += b_lo(hp[n]) + b_hi(hp[n]);
      s[0] = quad_sum(s[0]) * (1.f / 64);
      s[1] = quad_sum(s[1]) * (1.f / 64);
#pragma unroll
      for (int n = 0; n < 16; n++) {
        const float d0 = b_lo(hp[n]) - s[n & 1], d1 = b_hi(hp[n]) - s[n & 1];
        v[n & 1] = fmaf(d0, d0, fmaf(d1, d1, v[n & 1]));
      }
      v[0] = quad_sum(v[0]);
      v[1] = quad_sum(v[1]);
      if (c4 < 2) st_tag2(g_st2 + j * NS + 128 * g + rl + 8 * c4, c4 ? s[1] : s[0], c4 ? v[1] : v[0], par);
      PMARK(wg, 9);
    }
    GMARK(19);
  } else if (half == 0) {
    const int t = rank && (tid & 127) >= 96 ? 0 : tid & 127;
    const uint32_t* wp = reinterpret_cast<const uint32_t*>(w1 + (size_t)(28 * g) * NF + 448 * ii + 256 * rank) + t;
    float s0 = 0.f, s1 = 0.f;
#pragma unroll 14
    for (int k = 0; k < 28; k++) {
      const uint32_t v = __ldg(wp + k * (NF / 2));
      s0 += b_lo(v);
      s1 += b_hi(v);
    }
    st_tag2(g_cs1 + (j * 16 + g) * 128 + t, s0, s1, par);
    mbar_wait(sb, B_OFULL);
    s0 = s1 = 0.f;
#pragma unroll 1
    for (int k0 = 0; k0 < 16; k0 += 8) {
      const uint2* p = g_cs1 + (j * 16 + k0) * 128 + t;
      uint2 v[8];
      uint32_t bad;
      do {
        bad = 0;
#pragma unroll
        for (int k = 0; k < 8; k++) v[k] = ld_rlx2(p + 128 * k);
#pragma unroll
        for (int k = 0; k < 8; k++) bad |= (v[k].x ^ par) | (v[k].y ^ par);
      } while ((bad & 1u) != 0 && !timed_out(sb));
#pragma unroll
      for (int k = 0; k < 8; k++) { s0 += __uint_as_float(v[k].x); s1 += __uint_as_float(v[k].y); }
    }
    sts_f2(sb + SM_CS1 + 8 * t, s0, s1);
    __syncwarp();
    if (lane == 0) mbar_arrive(bar + 8 * B_CS1);
    PMARK(wg, 9);
  }
  const int oc = rank ? 3 + 2 * pair : 2 * pair, orow = rl + 8 * (ii >> 1);
  uint32_t res[8];
  {
    float acc[64];
    const bool wide = pair || !rank;
    if (wide) ffn_loop<true, false>(acc, sb, j, rank, pair, half PROF_ARG);
    else ffn_loop<false, false>(acc, sb, j, rank, pair, half PROF_ARG);
#pragma unroll
    for (int n = 0; n < 8; n++)
      res[n] = lds_u32(sb + SM_A + (oc + (n >> 2)) * 16384 + orow * 128 + (((4 * (ii & 1) + (n & 3)) ^ (orow & 7)) << 4) + 4 * c4);
    mbar_wait(sb, B_CS1);
    const float2 st0 = lds_f2(sb + SM_ST + 8 * rl), st1 = lds_f2(sb + SM_ST + 8 * rl + 64);
    const float mu[2] = {st0.x, st1.x}, hr[2] = {st0.y, st1.y};
    PMARK(wg, 21);
    wg_wait<0>();
    pin(acc);
    PMARK(wg, 12); GMARK(20);
    if (lane == 0) {
      mbar_arrive(bar + 8 * (B_WREL + 12 + pair));
      mbar_arrive(bar + 8 * B_AFREE3_L);
      mbar_arrive_remote(mapa(bar + 8 * B_AFREE3_R, rank ^ 1));
    }
    const int kap0 = rank ? 4 + pair : 2 * pair;
    float cur[32];
#pragma unroll
    for (int n = 0; n < 32; n++) asm volatile("mov.b32 %0, %1;" : "=f"(cur[n]) : "f"(acc[n]));
#pragma unroll 1
    for (int a = 0; a <= (int)wide; a++) {
      uint32_t gp[16];
      const uint32_t csb = sb + SM_CS1 + (kap0 - 4 * rank + a) * 256 + 8 * c4;
#pragma unroll
      for (int n = 0; n < 8; n++) {
        const float2 cs = lds_f2(csb + 32 * n);
        float z[4] = {fmaf(-mu[0], cs.x, cur[4 * n]) * hr[0], fmaf(-mu[0], cs.y, cur[4 * n + 1]) * hr[0],
                      fmaf(-mu[1], cs.x, cur[4 * n + 2]) * hr[1], fmaf(-mu[1], cs.y, cur[4 * n + 3]) * hr[1]};
#pragma unroll
        for (int e = 0; e < 4; e++) {
          float th;
          asm("tanh.approx.f32 %0, %1;" : "=f"(th) : "f"(z[e]));
          z[e] = fmaf(z[e], th, z[e]);
        }
        gp[2 * n] = pack_b2(z[0], z[1]);
        gp[2 * n + 1] = pack_b2(z[2], z[3]);
      }
      mbar_wait(sb, B_AFREE3_L);
#pragma unroll
      for (int n = 0; n < 4; n++) stsm4(sb + SM_A + (kap0 + a) * 16384 + (soff ^ (32 * n)), gp[4 * n], gp[4 * n + 1], gp[4 * n + 2], gp[4 * n + 3]);
      fence_async_smem();
      __syncwarp();
      if (lane == 0) mbar_arrive(bar + 8 * (B_GFULL + kap0 + a));
#pragma unroll
      for (int n = 0; n < 32; n++) asm volatile("mov.b32 %0, %1;" : "=f"(cur[n]) : "f"(acc[32 + n]));
    }
    PMARK(wg, 13); GMARK(21);
  }
  const bool wide = !pair || rank;
  uint4* pbase = g_part + (size_t)((g * 2 + rank) * 16) * 1024 + wg * 256 + (fresh_tid() & 127);
  __nv_bfloat16* op = out + (size_t)(128 * g + orow) * ND + 64 * oc + 32 * (ii & 1) + 2 * (fresh_lane() & 3);
  asm volatile("" : "+l"(pbase), "+l"(op));
  float acc[64];
  if (wide) ffn_loop<true, true>(acc, sb, 4 * rank, rank, pair, half PROF_ARG);
  else ffn_loop<false, true>(acc, sb, 4 * rank, rank, pair, half PROF_ARG);
  wg_wait<0>();
  pin(acc);
  PMARK(wg, 14); GMARK(22);
  asm volatile("barrier.cluster.arrive.relaxed.aligned;" ::: "memory");
#pragma unroll
  for (int a = 0; a < 2; a++) {
#pragma unroll
    for (int o = 0; o < 4; o++) {
      const int i0 = 32 * a + 16 * (o & 1) + 2 * (o >> 1);
      st_rec_if(o != ii && (a == 0 || wide), pbase + ii * 1024 + o * 4096 + a * 128, pack_b2(acc[i0], acc[i0 + 1]) | 1u,
                pack_b2(acc[i0 + 4], acc[i0 + 5]), pack_b2(acc[i0 + 8], acc[i0 + 9]), pack_b2(acc[i0 + 12], acc[i0 + 13]));
    }
  }
  float own[16];
#pragma unroll
  for (int k = 0; k < 16; k++) {
    const int i0 = 32 * (k >> 3) + 4 * ((k >> 1) & 3) + (k & 1);
    const float lo = (ii & 2) ? acc[i0 + 2] : acc[i0], hi = (ii & 2) ? acc[i0 + 18] : acc[i0 + 16];
    own[k] = (ii & 1) ? hi : lo;
  }
#pragma unroll
  for (int k = 0; k < 8; k++) {
    own[2 * k] += b_lo(res[k]);
    own[2 * k + 1] += b_hi(res[k]);
  }
  pin(own);
  PMARK(wg, 24);
  uint4 in[6];
  const uint4* src = pbase + ii * 4096;
  do {
#pragma unroll
    for (int u = 0; u < 6; u++) in[u] = ld_rec(src + ((ii + 1 + (u >> 1)) & 3) * 1024 + (u & 1) * (wide ? 128 : 0));
  } while ((in[0].x & in[1].x & in[2].x & in[3].x & in[4].x & in[5].x & 1u) == 0 && !timed_out(sb));
  PMARK(wg, 25);
#pragma unroll
  for (int a = 0; a < 2; a++) {
    if (a == 0 || wide) {
      uint32_t w4[4];
#pragma unroll
      for (int k = 0; k < 4; k++) {
        float lo = own[8 * a + 2 * k], hi = own[8 * a + 2 * k + 1];
#pragma unroll
        for (int u = 0; u < 3; u++) {
          const uint4 v = in[2 * u + a];
          const uint32_t w = k == 0 ? v.x : k == 1 ? v.y : k == 2 ? v.z : v.w;
          lo += b_lo(w);
          hi += b_hi(w);
        }
        w4[k] = pack_b2(lo, hi);
      }
      const int ln = fresh_lane();
#pragma unroll
      for (int d = 1; d <= 2; d <<= 1) {
#pragma unroll
        for (int k = 0; k < 4; k++) {
          if (k & d) continue;
          const uint32_t r = __shfl_xor_sync(0xffffffffu, (ln & d) ? w4[k] : w4[k + d], d);
          if (ln & d) w4[k] = r; else w4[k + d] = r;
        }
      }
      *reinterpret_cast<uint4*>(op + 64 * a + 6 * (ln & 3)) = make_uint4(w4[0], w4[1], w4[2], w4[3]);
    }
  }
  PMARK(wg, 15); GMARK(23);
  PDUMP(wg);
}

__global__ void __cluster_dims__(2, 1, 1) __launch_bounds__(NTHREADS, 1)
fused_block_kernel(const __grid_constant__ CUtensorMap tmX, const __grid_constant__ CUtensorMap tmWq, const __grid_constant__ CUtensorMap tmWo,
                   const __grid_constant__ CUtensorMap tmW1, const __grid_constant__ CUtensorMap tmW2,
                   const __nv_bfloat16* __restrict__ x, const __nv_bfloat16* __restrict__ wqkv, const __nv_bfloat16* __restrict__ wo,
                   const __nv_bfloat16* __restrict__ w1, const __nv_bfloat16* __restrict__ w2, __nv_bfloat16* __restrict__ out) {
  extern __shared__ __align__(1024) unsigned char smem[];
  const uint32_t sb = (uint32_t)__cvta_generic_to_shared(smem);
  const uint32_t bar = sb + SM_BAR;
  const int tid = threadIdx.x, warp = tid >> 5;
  const int b = blockIdx.x, rank = b & 1;
  const int h = b & 15, r = b >> 4, g = b >> 3, j = b & 7;
  const int odd = h & 1, wcol0 = 28 * h - 4 * odd;
  constexpr uint32_t st_stage = SM_W + 6 * 12288;
  if (warp == 16) {
    if (elect_one()) {
      asm volatile("prefetch.tensormap [%0];" ::"l"(&tmWq) : "memory");
      asm volatile("prefetch.tensormap [%0];" ::"l"(&tmX) : "memory");
#pragma unroll
      for (int i = 0; i < B_KVFULL; i++) mbar_init(bar + 8 * i, bar_count(i, 0, 0));
      uint32_t t;
      asm volatile("mov.u32 %0, %%clock;" : "=r"(t));
      sts_u32(sb + SM_EP + 16, t);
      asm volatile("fence.mbarrier_init.release.cluster;" ::: "memory");
      fence_async_smem();
    }
    __syncwarp();
    asm volatile("barrier.cluster.arrive.relaxed.aligned;" ::: "memory");
    if (elect_one()) {
      mbar_expect(bar + 8 * B_WQ, 12288);
      tma3d(sb + SM_W, &tmWq, wcol0, 0, 0, bar + 8 * B_WQ);
#pragma unroll
      for (int c = 0; c < 13; c++) mbar_expect(bar + 8 * (c < 7 ? B_XFULL + c : B_WQ + c - 6), c < 7 ? 32768 : 12288);
    }
    __syncwarp();
    asm volatile("bar.arrive 1, 640;" ::: "memory");
    PMARK(4, 2);
    asm volatile("barrier.cluster.wait.acquire.aligned;" ::: "memory");
    if (elect_one()) {
#pragma unroll 1
      for (int c = 0; c < 7; c++) {
        if (c >= 4) mbar_wait(sb, B_XREL + c - 4);
        tma2d_mc(sb + (c & 3) * 32768 + rank * 16384, &tmX, 64 * c, 256 * r + 128 * rank, bar + 8 * (B_XFULL + c));
        if (c == ST_POS) {
          mbar_expect(bar + 8 * B_ST, 16 + 16 * 896);
          bulk_g2s(sb + SM_EP, g_epoch + b, 16, bar + 8 * B_ST);
          bulk_g2s(sb + st_stage, x + (size_t)(256 * r + 16 * h) * ND, 16 * 896, bar + 8 * B_ST);
        }
        if (c == 5) mbar_wait(sb, B_STDONE);
        if (c < 6) tma3d(sb + SM_W + (c + 1) * 12288, &tmWq, wcol0, 64 * (c + 1), 0, bar + 8 * (B_WQ + c + 1));
      }
    }
    __syncwarp();
    PMARK(4, 0);
  } else {
    asm volatile("barrier.cluster.arrive.relaxed.aligned;" ::: "memory");
    bar_sync(1, 640);
    if (warp > 16) {
      const int lane = tid & 31;
      const uint4* sp = reinterpret_cast<const uint4*>(g_st1 + 256 * r) + lane;
      uint4 sv[4];
      float cs[8] = {};
#pragma unroll 1
      for (int c = 0; c < 7; c++) {
        if (c == ST_USE && warp != 18) {
          mbar_wait(sb, B_ST);
          const int row = 4 * (warp - 17) + (lane >> 2);
          const uint32_t src = sb + st_stage + row * 896;
          const float piv = b_lo(lds_u32(src));
          float s1 = 0.f, s2 = 0.f;
#pragma unroll 2
          for (int k = 0; k < 14; k++) {
            const uint4 v = lds_u4(src + 64 * k + 16 * (lane & 3));
            const uint32_t w[4] = {v.x, v.y, v.z, v.w};
#pragma unroll
            for (int e = 0; e < 4; e++) {
              const float d0 = b_lo(w[e]) - piv, d1 = b_hi(w[e]) - piv;
              s1 += d0 + d1;
              s2 = fmaf(d0, d0, fmaf(d1, d1, s2));
            }
          }
          const float m = quad_sum(s1) * (1.f / ND);
          s2 = quad_sum(s2);
          if (lane == 0) mbar_arrive(bar + 8 * B_STDONE);
          if ((lane & 3) == 0)
            st_tag2(g_st1 + 256 * r + 16 * h + row, piv + m, rsqrtf(fmaxf(fmaf(-m, m, s2 * (1.f / ND)), 0.f) + 1e-5f), epoch(sb) & 1);
          if (warp == 17) PMARK(6, 2);
        }
        if (c == ST_POLL && warp == 18) {
#pragma unroll
          for (int k = 0; k < 4; k++) sv[k] = ld_rec(sp + 32 * k);
        }
        mbar_wait(sb, B_WQ + c);
        const uint32_t src = sb + SM_W + c * 12288 + (warp - 17) * 4096 + (lane >> 2) * 64 + (((lane & 3) ^ (lane >> 3)) << 4);
        uint4 v[8];
#pragma unroll
        for (int k = 0; k < 8; k++) v[k] = lds_u4(src + 512 * k);
#pragma unroll
        for (int k = 0; k < 8; k++) {
          cs[0] += b_lo(v[k].x); cs[1] += b_hi(v[k].x); cs[2] += b_lo(v[k].y); cs[3] += b_hi(v[k].y);
          cs[4] += b_lo(v[k].z); cs[5] += b_hi(v[k].z); cs[6] += b_lo(v[k].w); cs[7] += b_hi(v[k].w);
        }
      }
#pragma unroll
      for (int n = 4; n; n >>= 1) {
        const bool up = lane & (4 * n);
#pragma unroll
        for (int e = 0; e < n; e++) cs[e] = (up ? cs[e + n] : cs[e]) + __shfl_xor_sync(0xffffffffu, up ? cs[e] : cs[e + n], 4 * n);
      }
      sts_u32(sb + SM_CS0 + (warp - 17) * 128 + 32 * (lane & 3) + (lane & 28), __float_as_uint(cs[0]));
      if (warp == 18) {
        mbar_wait(sb, B_ST);
        const uint32_t par = epoch(sb) & 1;
        while (true) {
          uint32_t bad = 0;
#pragma unroll
          for (int k = 0; k < 4; k++) bad |= (sv[k].x ^ par) | (sv[k].y ^ par) | (sv[k].z ^ par) | (sv[k].w ^ par);
          if ((bad & 1u) == 0 || timed_out(sb)) break;
#pragma unroll
          for (int k = 0; k < 4; k++) sv[k] = ld_rec(sp + 32 * k);
        }
#pragma unroll
        for (int k = 0; k < 4; k++)
          asm volatile("st.shared.v4.u32 [%0], {%1, %2, %3, %4};" ::"r"(sb + SM_ST + 16 * lane + 512 * k), "r"(sv[k].x), "r"(sv[k].y), "r"(sv[k].z), "r"(sv[k].w) : "memory");
      }
      __syncwarp();
      if (lane == 0) mbar_arrive(bar + 8 * (B_CS0 + warp - 17));
      if (warp == 18) PMARK(6, 0);
    }
  }

  if (warp >= 16) {
    asm volatile("setmaxnreg.dec.sync.aligned.u32 32;");
    if (warp == 16) {
      const int w1c0 = 448 * (j >> 1) + 256 * rank;
      if (elect_one()) {
        mbar_wait(sb, B_KVREL + 1);
        l2_prefetch((const char*)wo + b * 3136, 3136);
        l2_prefetch((const char*)w1 + b * 12544, 12544);
        l2_prefetch((const char*)w2 + b * 12544, 12544);
        mbar_wait(sb, B_KVREL + 4);
        if (j < 7) {
          mbar_expect(bar + 8 * B_WOFULL, 7 * 8192);
#pragma unroll 1
          for (int c = 0; c < 7; c++) tma2d(sb + SM_W + c * 8192, &tmWo, 64 * j, 64 * c, bar + 8 * B_WOFULL);
        }
        uint32_t fb = bar + 8 * B_WFULL;
#pragma unroll 1
        for (int s = 0; s < 14; s++, fb += 8) {
          const int col = w1c0 + ((s & 1) ? 128 - 64 * rank : 0), row = 64 * hchunk(j, s >> 1);
          const uint32_t dst = sb + wslot(s);
          if (s >= 2 && s != 5) mbar_wait(sb, s < 4 ? B_WOREL + s - 2 : s == 4 ? B_WODONE : B_WREL + s - 6);
          tma2d(dst, &tmW1, col, row, fb);
          if ((s & 1) || !rank) tma2d(dst + 8192, &tmW1, col + 64, row, fb);
          PSTAGE(0, s);
        }
        const int row2 = 448 * (j >> 1), col2 = rank ? 192 : 0;
#pragma unroll 1
        for (int u = 0; u < 14; u++, fb += 8) {
          const int n = 4 - rank, pair = u < 2 * n ? (u & 1) : (u - 7 >= n);
          const int row = row2 + 64 * wrap7(4 * rank + (u < 2 * n ? (u >> 1) : u - n - pair * (7 - n))), col = col2 + 128 * pair;
          const uint32_t dst = sb + f2slot(rank, u) * 8192;
          mbar_wait(sb, B_WREL + f2dep(rank, u));
          tma2d(dst, &tmW2, col, row, fb);
          if (!pair || rank) tma2d(dst + 8192, &tmW2, col + 64, row, fb);
          PSTAGE(0, 14 + u);
        }
        PMARK(4, 7);
      }
      __syncwarp();
      if (elect_one()) g_epoch[b].x = epoch(sb);
    } else if (warp == 17) {
      const int lane = fresh_lane();
      bar_sync(7, 128);
      asm volatile("barrier.cluster.wait.acquire.aligned;" ::: "memory");
      mbar_wait(sb, B_ST);
      const uint32_t ep = 2 * epoch(sb);
#pragma unroll 1
      for (int i = B_KVFULL + 2 + lane; i < B_AFREE3_L; i += 32) {
        uint32_t bytes = 0;
        if (i < B_KVREL) bytes = 16384 + 16 * ((i - B_KVFULL) & 1);
        else if ((i >= B_OFULL && i < B_WOFULL) || (i >= B_HFULL && i < B_WFULL && i != B_HFULL + j) || (i >= B_GFULL && (i - B_GFULL >= 4) != (rank == 1))) bytes = 16384;
        else if (i >= B_WFULL && i < B_WREL) {
          const int pair = stage_pair(rank, i - B_WFULL);
          bytes = (i - B_WFULL < 14 ? (pair || !rank) : (!pair || rank)) ? 16384 : 8192;
        }
        if (bytes) mbar_expect(bar + 8 * i, bytes);
      }
#pragma unroll 1
      for (int rd = 0; rd < 7; rd++) {
        const uint32_t* flag = rd < 5 ? g_flagKV + (h * 8 + ((r + max(lane, 1)) & 7)) * 8 : (rd == 5 ? g_flagO : g_flagH) + (g * 8 + (lane & 7)) * 8;
        const uint32_t target = rd == 5 ? 2 * ep : ep - (rd == 0 && lane == 0);
        uint32_t todo = rd == 0 ? 15u : rd < 5 ? 8u << rd : 0x55u << rank;
        if (rd == 6) todo &= 0x7Fu & ~(3u << (j & 6));
        mbar_wait(sb, rd > 5 ? B_AFREE2 : rd == 5 ? B_KVREL + 7 : rd > 0 ? B_KVREL + rd : B_KVFULL + 1);
        if (rd == 5) PMARK(5, 3);
        if (rd == 6) PMARK(5, 5);
        do {
          uint32_t rdy = todo & __ballot_sync(0xffffffffu, (int)(ld_flag(flag) - target) >= 0);
          if (rd == 5) rdy &= mbar_test(sb, B_AFREE1) ? (mbar_test(sb, B_OSTG) ? 0xFFu : 0xBFu) : 0u;
          if (rd == 0) { const uint32_t nr = todo & ~rdy; rdy &= (nr & (0u - nr)) - 1; }
          todo &= ~rdy;
          fence_async_all();
          for (; rdy; rdy &= rdy - 1) {
            const int k = __ffs(rdy) - 1;
            if (elect_one()) {
              if (rd < 5) {
                const int bk = max(k, 1);
                const unsigned char* src = g_kv + (size_t)(h * 8 + ((r + bk) & 7)) * 32896;
                const uint32_t dst = sb + ((bk + 2) % 3) * 32768, fb = bar + 8 * (B_KVFULL + 2 * bk);
                if (k != 1) bulk_g2s(dst, src, 16384, fb);
                if (k != 0) {
                  bulk_g2s(dst + 16384, src + 16384, 16384, fb + 8);
                  bulk_g2s(sb + SM_TR + 16 * k, src + 32768, 16, fb + 8);
                }
              } else {
                const unsigned char* src = rd == 5 ? g_O + (size_t)(g * 8 + k) * 16384 : g_h + (size_t)(g * 7 + k) * 16384;
                bulk_g2s_mc(sb + SM_A + k * 16384, src, 16384, bar + 8 * ((rd == 5 ? B_OFULL : B_HFULL) + k));
              }
            }
            __syncwarp();
            if (rd == 0 && k == 0) PMARK(5, 2);
          }
        } while (todo && !timed_out(sb));
        if (rd == 5) PMARK(5, 4);
      }
      PMARK(5, 6);
      if (elect_one()) {
        mbar_wait(sb, B_AFREE3_R);
#pragma unroll 1
        for (int k = 4 * rank; k < 4 + 3 * rank; k++) {
          mbar_wait(sb, B_GFULL + k);
          const uint32_t src = sb + SM_A + k * 16384;
          bulk_s2peer(mapa(src, rank ^ 1), src, 16384, mapa(bar + 8 * (B_GFULL + k), rank ^ 1));
        }
      }
      __syncwarp();
      PMARK(5, 7);
      PDUMP(5);
    } else {
      const int lane = fresh_lane();
      asm volatile("barrier.cluster.wait.acquire.aligned;" ::: "memory");
      bar_sync(7, 128);
      if (warp == 19) {
        if (elect_one()) {
          unsigned char* dst = g_kv + (size_t)(h * 8 + r) * 32896;
          uint32_t* flag = g_flagKV + (h * 8 + r) * 8;
          mbar_wait(sb, B_KVFULL);
          const uint32_t ep = 2 * epoch(sb);
          bulk_s2g(dst, sb + SM_KV0, 16384);
          bulk_commit_wait();
          fence_async_all();
          asm volatile("st.relaxed.gpu.global.u32 [%0], %1;" ::"l"(flag), "r"(ep - 1) : "memory");
          PMARK(5, 0);
          mbar_wait(sb, B_KVFULL + 1);
          bulk_s2g(dst + 16384, sb + SM_KV0 + 16384, 16384);
          mbar_wait(sb, B_TRDONE);
          fence_async_smem();
          bulk_s2g(dst + 32768, sb + SM_TR, 16);
          bulk_commit_wait();
          fence_async_all();
          asm volatile("st.relaxed.gpu.global.u32 [%0], %1;" ::"l"(flag), "r"(ep) : "memory");
          PMARK(5, 1);
        }
        __syncwarp();
#pragma unroll
        for (int k = 0; k < 4; k++) asm volatile("st.shared.v4.u32 [%0], {%1, %1, %1, %1};" ::"r"(sb + SM_ZERO + 512 * k + 16 * lane), "r"(0) : "memory");
        fence_async_smem();
        __syncwarp();
        if (elect_one()) {
          mbar_wait(sb, B_KVREL + 3);
          uint4* inbox = g_part + (size_t)((g * 2 + rank) * 16 + (j >> 1) * 4) * 1024;
#pragma unroll 1
          for (int k = 0; k < 32; k++)
            if ((k >> 3) != (j >> 1)) bulk_s2g(inbox + 128 * k, sb + SM_ZERO, 2048);
          bulk_commit_wait();
          fence_async_all();
          mbar_arrive(bar + 8 * B_AFREE1);
          mbar_arrive_remote(mapa(bar + 8 * B_AFREE1, rank ^ 1));
        }
        __syncwarp();
      }
      const uint32_t par = epoch(sb) & 1;
      mbar_wait(sb, B_HFULL + hchunk(j, 2));
#pragma unroll 1
      for (int row = lane + 32 * (warp - 18); row < 128; row += 64) {
        const uint2* p = g_st2 + 128 * g + row;
        uint2 v[7];
        uint32_t bad;
        do {
          bad = 0;
#pragma unroll
          for (int k = 0; k < 7; k++) v[k] = ld_rlx2(p + k * NS);
#pragma unroll
          for (int k = 0; k < 7; k++) bad |= (v[k].x ^ par) | (v[k].y ^ par);
        } while ((bad & 1u) != 0 && !timed_out(sb));
        float mu = 0.f, m2 = 0.f;
#pragma unroll
        for (int k = 0; k < 7; k++) mu += __uint_as_float(v[k].x);
        mu *= 1.f / 7;
#pragma unroll
        for (int k = 0; k < 7; k++) {
          const float d = __uint_as_float(v[k].x) - mu;
          m2 += fmaf(64.f * d, d, __uint_as_float(v[k].y));
        }
        sts_f2(sb + SM_ST + 8 * row, mu, 0.5f * rsqrtf(m2 * (1.f / ND) + 1e-5f));
      }
      __syncwarp();
      if (lane == 0) mbar_arrive(bar + 8 * B_CS1);
      if (warp == 18) PMARK(6, 1);
      if (warp == 18) PDUMP(6);
      return;
    }
    asm volatile("barrier.cluster.arrive.relaxed.aligned;\nbarrier.cluster.wait.acquire.aligned;" ::: "memory");
    return;
  }

  uint32_t q[8];
  float gd[5];
  {
    const int lane = fresh_lane(), wg = uniform_wg(), warp4 = warp & 3, c4 = lane & 3;
    if (warp == 15 && elect_one()) {
#pragma unroll
      for (int i = B_KVFULL; i < B_COUNT; i++) mbar_init(bar + 8 * i, bar_count(i, j, rank));
      sts_f2(sb + SM_TR, 0.f, 0.f);
      asm volatile("fence.mbarrier_init.release.cluster;" ::: "memory");
      fence_async_smem();
    }
    __syncwarp();
    if (warp == 15) asm volatile("bar.arrive 7, 128;" ::: "memory");
    const int rowl = 64 * wg + 16 * warp4 + (lane >> 2);
    float acc[48];
#pragma unroll 1
    for (int c = 0; c < 7; c++) {
      const uint64_t da = mkdesc(sb + (c & 3) * 32768 + wg * 8192, 16, 1024, 1);
      const uint64_t db = mkdesc(sb + SM_W + c * 12288, 4096, 512, 2);
      mbar_wait(sb, B_WQ + c);
      mbar_wait(sb, B_XFULL + c);
      if (c == 0) { PMARK(wg, 1); GMARK(16); }
      wg_fence();
#pragma unroll
      for (int k = 0; k < 4; k++) mma_ss_n96_bf16_f32(acc, dadd(da, 32 * k), dadd(db, 1024 * k), (c | k) != 0);
      wg_commit();
      if (c == 0) asm volatile("barrier.cluster.wait.acquire.aligned;" ::: "memory");
      wg_wait<1>();
      if (c >= 1 && c <= 4 && lane == 0) {
        mbar_arrive(bar + 8 * (B_XREL + c - 1));
        if (c < 4) mbar_arrive_remote(mapa(bar + 8 * (B_XREL + c - 1), rank ^ 1));
      }
    }
    mbar_wait(sb, B_CS0 + 1);
    const float2 st0 = lds_f2(sb + SM_ST + 8 * rowl), st1 = lds_f2(sb + SM_ST + 8 * rowl + 64);
    const float m0 = st0.x, m1 = st1.x, r0 = st0.y, r1 = st1.y;
    PMARK(wg, 16);
    mbar_wait(sb, B_XREL + 3);
    PMARK(wg, 17);
    wg_wait<0>();
    pin(acc);
    PMARK(wg, 2); GMARK(17);
    const bool padA = odd && c4 < 2, padB = !odd && c4 >= 2;
    float n0 = 0.f, n1 = 0.f, vm = 0.f;
    auto finish = [&](int n, float ra, float rb, uint32_t& p0, uint32_t& p1) {
      const float2 cs = lds_f2(sb + SM_CS0 + 32 * n + 8 * c4);
      if (((n & 3) == 0 && padA) || ((n & 3) == 3 && padB)) ra = rb = 0.f;
      float z0 = fmaf(-m0, cs.x, acc[4 * n]) * ra, z1 = fmaf(-m0, cs.y, acc[4 * n + 1]) * ra;
      float z2 = fmaf(-m1, cs.x, acc[4 * n + 2]) * rb, z3 = fmaf(-m1, cs.y, acc[4 * n + 3]) * rb;
      if (n < 8) {
        n0 = fmaf(z0, z0, fmaf(z1, z1, n0));
        n1 = fmaf(z2, z2, fmaf(z3, z3, n1));
      } else {
        vm = fmaxf(fmaxf(vm, fmaxf(fabsf(z0), fabsf(z1))), fmaxf(fabsf(z2), fabsf(z3)));
        if ((n == 8 && odd && c4 == 0) || (n == 11 && !odd && c4 == 2)) z0 = z2 = 1.f;
      }
      p0 = pack_h2(z0, z1);
      p1 = pack_h2(z2, z3);
    };
    uint32_t pk[16];
#pragma unroll
    for (int n = 4; n < 12; n++) {
      if (n == 8) mbar_wait(sb, B_CS0 + 2);
      finish(n, r0, r1, pk[2 * n - 8], pk[2 * n - 7]);
    }
    const int srow = 64 * wg + 16 * warp4 + (lane & 7) + 8 * ((lane >> 3) & 1);
    const uint32_t sa = sb + SM_KV0 + (srow + (srow & 128)) * 64 + (((lane >> 4) ^ ((srow >> 1) & 3)) << 4);
#pragma unroll
    for (int n = 0; n < 4; n++) stsm4((sa ^ (32 * (n & 1))) + 8192 * (n >> 1), pk[4 * n], pk[4 * n + 1], pk[4 * n + 2], pk[4 * n + 3]);
    fence_async_smem();
    __syncwarp();
    if (lane == 0) mbar_arrive(bar + 8 * (B_KVFULL + (wg >> 1)));
    const float k0 = n0, k1 = n1;
    n0 = n1 = 0.f;
    mbar_wait(sb, B_CS0);
#pragma unroll
    for (int n = 0; n < 4; n++) finish(n, r0 * 0.27264365f, r1 * 0.27264365f, q[2 * n], q[2 * n + 1]);
    gd[0] = k0; gd[1] = k1; gd[2] = n0; gd[3] = n1; gd[4] = vm;
    PMARK(wg, 3);
  }
  asm volatile("setmaxnreg.inc.sync.aligned.u32 112;");
  PMARK(threadIdx.x >> 7, 27);
  {
    float o[16];
    uint32_t sc[32], oh[8];
#pragma unroll
    for (int i = 0; i < 16; i++) o[i] = 0.f;
    uint64_t kd = mkdesc(sb + SM_KV0, 16, 512, 2);
    mbar_wait(sb, B_KVFULL);
    PMARK(threadIdx.x >> 7, 29);
    pin(q);
    wg_fence();
    mma_rs_n128_f16_f16<0>(sc, q[0], q[1], q[2], q[3], kd);
    mma_rs_n128_f16_f16<1>(sc, q[4], q[5], q[6], q[7], dadd(kd, 32));
    wg_commit();
    {
      const int ka = __float_as_int(quad_sum(gd[0])), kb = __float_as_int(quad_sum(gd[1]));
      const int qa = __float_as_int(quad_sum(gd[2])), qb = __float_as_int(quad_sum(gd[3]));
      const int km = __reduce_max_sync(0xffffffffu, max(ka & 0x7fffffff, kb & 0x7fffffff));
      const int vmx = __reduce_max_sync(0xffffffffu, __float_as_int(gd[4]));
      sts_u32(sb + SM_RED + 4 * fresh_tid(), max(qa & 0x7fffffff, qb & 0x7fffffff));
      if (fresh_lane() == 0) {
        asm volatile("red.shared.max.s32 [%0], %1;" ::"r"(sb + SM_TR), "r"(km) : "memory");
        asm volatile("red.shared.max.s32 [%0], %1;" ::"r"(sb + SM_TR + 4), "r"(vmx) : "memory");
        mbar_arrive(bar + 8 * B_TRDONE);
      }
    }
    wg_wait<0>();
    pin(sc);
    PMARK(threadIdx.x >> 7, 4);
    uint32_t nslot = 0;
#pragma unroll 1
    for (int blk = 0; blk < 8; blk++) {
      attn_tile<1>(sc, oh, q, dadd(kd, 16384), dadd(kd, 8192), sb, B_KVFULL + 2 * blk + 1, blk & FLUSH_MASK);
      const uint64_t kn = blk < 7 ? mkdesc(sb + nslot, 16, 512, 2) : kd;
      nslot = nslot == 65536 ? 0 : nslot + 32768;
      attn_tile<0>(sc, oh, q, kn, dadd(kd, 16384 + 8192), sb, B_KVFULL + (blk < 7 ? 2 * blk + 2 : 15), 1);
      if (fresh_lane() == 0) mbar_arrive(bar + 8 * (B_KVREL + blk));
      if ((blk & FLUSH_MASK) == FLUSH_MASK) {
#pragma unroll
        for (int i = 0; i < 8; i++) {
          const float2 f = __half22float2(*reinterpret_cast<const __half2*>(&oh[i]));
          o[2 * i] += f.x;
          o[2 * i + 1] += f.y;
        }
      }
      kd = kn;
    }
    const int tid = fresh_tid(), lane = tid & 31, wg = tid >> 7, warp4 = (tid >> 5) & 3, c4 = lane & 3;
    const float qn2 = __uint_as_float(lds_u32(sb + SM_RED + 4 * tid));
    PMARK(wg, 5); GMARK(18);
    if (lane == 0) {
      mbar_arrive(bar + 8 * B_AFREE1);
      mbar_arrive_remote(mapa(bar + 8 * B_AFREE1, rank ^ 1));
    }
    const int src = (lane & 28) | (odd ? 0 : 2);
    const float l0 = __shfl_sync(0xffffffffu, odd ? o[0] : o[12], src), l1 = __shfl_sync(0xffffffffu, odd ? o[2] : o[14], src);
    const float2 tr = lds_f2(sb + SM_TR + 16 * (lane & 7));
    const float kn2 = __int_as_float(__reduce_max_sync(0xffffffffu, __float_as_int(tr.x)));
    const float vmx = __int_as_float(__reduce_max_sync(0xffffffffu, __float_as_int(tr.y)));
    float om = 0.f;
#pragma unroll
    for (int i = 0; i < 16; i++) om += fabsf(o[i]);
    const float lm = fminf(l0, l1);
    const bool ok = qn2 * kn2 <= 950.f && qn2 <= 1e6f && kn2 <= 1e6f && vmx <= 3e4f && vmx >= 2.5e-4f && om <= 1e30f && lm >= 0.03125f &&
                    lm * vmx >= 0.00390625f;
    const uint32_t stage = sb + SM_KV0 + wg * 4096;
    if (__all_sync(0xffffffffu, ok)) {
      const float i0 = __frcp_rn(l0), i1 = __frcp_rn(l1);
      uint32_t op[8];
#pragma unroll
      for (int n = 0; n < 4; n++) {
        const bool pad = (n == 0 && odd && c4 < 2) || (n == 3 && !odd && c4 >= 2);
        op[2 * n] = pad ? 0u : pack_b2(o[4 * n] * i0, o[4 * n + 1] * i0);
        op[2 * n + 1] = pad ? 0u : pack_b2(o[4 * n + 2] * i1, o[4 * n + 3] * i1);
      }
      const int srow = 16 * warp4 + (lane & 7) + 8 * ((lane >> 3) & 1);
      const uint32_t sa = stage + srow * 64 + (((lane >> 4) ^ ((srow >> 1) & 3)) << 4);
      stsm4(sa, op[0], op[1], op[2], op[3]);
      stsm4(sa ^ 32, op[4], op[5], op[6], op[7]);
    } else {
      attention_exact(x, wqkv, h, 256 * r + 64 * wg + 16 * warp4, stage + warp4 * 1024);
    }
    fence_async_smem();
    PMARK(wg, 18);
    bar_sync(2 + wg, 128);
    if (warp4 == 0 && elect_one()) {
      const int og = 2 * r + (wg >> 1);
      bulk_s2g(g_O + (size_t)(og * 16 + h) * 8192 + (wg & 1) * 4096, stage, 4096);
      mbar_arrive(bar + 8 * B_AFREE1);
      bulk_commit_wait();
      fence_async_all();
      red_add(g_flagO + (og * 8 + (h >> 1)) * 8);
      mbar_arrive(bar + 8 * B_OSTG);
      mbar_arrive_remote(mapa(bar + 8 * B_OSTG, rank ^ 1));
    }
    __syncwarp();
    PMARK(wg, 6);
  }
  phase_c(sb, g, j, x, w1, out PROF_ARG);
  asm volatile("barrier.cluster.wait.acquire.aligned;" ::: "memory");
}

typedef CUresult (*EncodeFn)(CUtensorMap*, CUtensorMapDataType, cuuint32_t, void*, const cuuint64_t*, const cuuint64_t*, const cuuint32_t*,
                             const cuuint32_t*, CUtensorMapInterleave, CUtensorMapSwizzle, CUtensorMapL2promotion, CUtensorMapFloatOOBfill);

void make2d(EncodeFn enc, CUtensorMap* tm, const void* p, int rows, int cols, int box_rows) {
  cuuint64_t dims[2] = {(cuuint64_t)cols, (cuuint64_t)rows}, str[1] = {(cuuint64_t)cols * 2};
  cuuint32_t box[2] = {64, (cuuint32_t)box_rows}, es[2] = {1, 1};
  enc(tm, CU_TENSOR_MAP_DATA_TYPE_BFLOAT16, 2, const_cast<void*>(p), dims, str, box, es, CU_TENSOR_MAP_INTERLEAVE_NONE,
      CU_TENSOR_MAP_SWIZZLE_128B, CU_TENSOR_MAP_L2_PROMOTION_L2_128B, CU_TENSOR_MAP_FLOAT_OOB_FILL_NONE);
}

}

extern "C" void kernel_launch(void* const* d_in, const int* in_sizes, int n_in, void* d_out, int out_size) {
  const __nv_bfloat16* x = (const __nv_bfloat16*)d_in[0];
  const __nv_bfloat16* wqkv = (const __nv_bfloat16*)d_in[1];
  const __nv_bfloat16* wo = (const __nv_bfloat16*)d_in[2];
  const __nv_bfloat16* w1 = (const __nv_bfloat16*)d_in[4];
  const __nv_bfloat16* w2 = (const __nv_bfloat16*)d_in[5];
  void* fn = nullptr;
  cudaDriverEntryPointQueryResult qr;
  cudaGetDriverEntryPoint("cuTensorMapEncodeTiled", &fn, cudaEnableDefault, &qr);
  EncodeFn enc = (EncodeFn)fn;
  CUtensorMap tmX, tmWq, tmWo, tmW1, tmW2;
  make2d(enc, &tmX, x, NS, ND, 128);
  make2d(enc, &tmWo, wo, ND, ND, 64);
  make2d(enc, &tmW1, w1, ND, NF, 64);
  make2d(enc, &tmW2, w2, NF, ND, 64);
  {
    cuuint64_t dims[3] = {ND, ND, 3}, str[2] = {3 * ND * 2, ND * 2};
    cuuint32_t box[3] = {32, 64, 3}, es[3] = {1, 1, 1};
    enc(&tmWq, CU_TENSOR_MAP_DATA_TYPE_BFLOAT16, 3, const_cast<__nv_bfloat16*>(wqkv), dims, str, box, es, CU_TENSOR_MAP_INTERLEAVE_NONE,
        CU_TENSOR_MAP_SWIZZLE_64B, CU_TENSOR_MAP_L2_PROMOTION_L2_128B, CU_TENSOR_MAP_FLOAT_OOB_FILL_NONE);
  }
  cudaFuncSetAttribute(fused_block_kernel, cudaFuncAttributeMaxDynamicSharedMemorySize, SM_TOTAL);
  fused_block_kernel<<<128, NTHREADS, SM_TOTAL, cudaStreamPerThread>>>(tmX, tmWq, tmWo, tmW1, tmW2, x, wqkv, wo, w1, w2,
                                                                         (__nv_bfloat16*)d_out);
}
```
